```python
import torch

def _softmax(x, axis=-1):
    return torch.softmax(x, dim=axis)
def _gelu(x):
    return torch.nn.functional.gelu(x, approximate="tanh")
def _silu(x):
    return torch.nn.functional.silu(x)
def _sigmoid(x):
    return torch.sigmoid(x)
def _layernorm(x, axis=-1, eps=1e-5):
    m = x.mean(dim=axis, keepdim=True)
    v = x.var(dim=axis, keepdim=True, unbiased=False)
    return (x - m) / torch.sqrt(v + eps)
def _scatter_add(tgt, idx, src, axis=0):
    return tgt.clone().index_add_(axis, idx, src)
def _segment_sum(src, seg, n):
    out = torch.zeros((n,) + src.shape[1:], dtype=src.dtype)
    return out.index_add_(0, seg, src)
def _pad(x, pw):
    flat = tuple(v for pair in reversed(pw) for v in pair)
    return torch.nn.functional.pad(x, flat)

kernel_name = 'gather_scatter__cheap_equivariant_egnn__graph'

def setup_inputs():

    _w = (lambda a: (lambda t: t.to(torch.bfloat16) if t.is_floating_point() else t)(torch.as_tensor(a)))
    N, deg, D, De = 25000, 32, 64, max(16, 1)
    E = N * deg
    return {
        "h": _w((lambda *s: torch.randn(*s, dtype=torch.bfloat16) * 0.2)(N, D)),
        "pos": _w((lambda *s: torch.randn(*s, dtype=torch.bfloat16) * 0.8)(N, 3)),
        "e_attr": _w((lambda *s: torch.randn(*s, dtype=torch.bfloat16) * 0.8)(E, De)),
        "src": _w((lambda lo, hi, *s: torch.randint(lo, hi, s))(0, N, E).to(torch.int64)),
        "dst": _w((lambda lo, hi, *s: torch.randint(lo, hi, s))(0, N, E).to(torch.int64)),
        "w_e": _w(0.1 * (lambda *s: torch.randn(*s, dtype=torch.bfloat16) * 0.8)(2 * D + 1 + De, D)),
        "w_x": _w(0.1 * (lambda *s: torch.randn(*s, dtype=torch.bfloat16) * 0.2)(D, 1)),
        "w_h": _w(0.1 * (lambda *s: torch.randn(*s, dtype=torch.bfloat16) * 0.2)(2 * D, D)),
    }

def reference(h, pos, e_attr, src, dst, w_e, w_x, w_h):
    N, D = h.shape[0], h.shape[1]
    diff = pos[dst] - pos[src]
    dist2 = torch.sum(diff * diff, axis=-1, keepdims=True)
    e_in = torch.concatenate([h[dst], h[src], dist2, e_attr], axis=-1)
    m_ij = _silu(e_in @ w_e)
    coord_scale = m_ij @ w_x
    pos_new = pos + _segment_sum(diff * coord_scale, dst, N)
    m_i = _segment_sum(m_ij, dst, N)
    h_new = h + _silu(torch.concatenate([h, m_i], axis=-1) @ w_h)
    return h_new, pos_new
```

```cpp
#include <cuda_runtime.h>
#include <cuda_bf16.h>
#include <cuda_fp16.h>
#include <stdint.h>

namespace {

constexpr int kN = 25000;
constexpr int kE = 800000;
constexpr int kG = 132;
constexpr int kNPC = 190;
constexpr int kChunk = 6064;
constexpr int kThreads = 384;
constexpr int kWarps = 12;
constexpr int kCapW = 336;
constexpr int kStages = 3;
constexpr int kStageBytes = 2560;
constexpr int kSegPerWarp = kG / kWarps;
constexpr uint32_t kBinMul = 22605092u;
constexpr int kDefExp = 4;
constexpr unsigned kSpinLimit = 1u << 24;

constexpr int SM_STAGE = 0;
constexpr int SM_REC = SM_STAGE;
constexpr int SM_WE = SM_STAGE + 49152;
constexpr int SM_LS = SM_STAGE + kWarps * kStages * kStageBytes;
constexpr int SM_LQ = SM_LS + kWarps * 2 * kCapW * 4;
constexpr int SM_WH = SM_LQ + kWarps * 2 * kCapW * 4;
constexpr int SM_H = SM_WH + 16384;
constexpr int SM_POS = SM_H + kWarps * 2048;
constexpr int SM_HIST = SM_POS + 208 * 8;
constexpr int SM_OFF = SM_HIST + 160 * 4;
constexpr int SM_WCNT = SM_OFF + 160 * 4;
constexpr int SM_SEG = SM_WCNT + 32 * 4;
constexpr int SM_MISC = SM_SEG + 136 * 4;
constexpr int SM_TOTAL = SM_MISC + 32;

__device__ uint4 g_tab[(kG * kNPC + 16) * 8];
__device__ uint4 g_rec[kG * kChunk / 2 + 64];
__device__ unsigned long long g_flag[kG * kG];
__device__ unsigned g_flag2[kG * kG];
__device__ unsigned g_epoch[kG];
#define TSTAMP(i)

__device__ __forceinline__ void mma_bf16(float (&c)[4], uint32_t a0, uint32_t a1, uint32_t a2, uint32_t a3, uint32_t b0, uint32_t b1) {
    asm("mma.sync.aligned.m16n8k16.row.col.f32.bf16.bf16.f32 {%0,%1,%2,%3}, {%4,%5,%6,%7}, {%8,%9}, {%0,%1,%2,%3};"
        : "+f"(c[0]), "+f"(c[1]), "+f"(c[2]), "+f"(c[3]) : "r"(a0), "r"(a1), "r"(a2), "r"(a3), "r"(b0), "r"(b1));
}
__device__ __forceinline__ void mma_f16_init(float (&c)[4], uint32_t a0, uint32_t a1, uint32_t a2, uint32_t a3, uint32_t b0, uint32_t b1) {
    asm("mma.sync.aligned.m16n8k16.row.col.f32.f16.f16.f32 {%0,%1,%2,%3}, {%4,%5,%6,%7}, {%8,%9}, {%10,%10,%10,%10};"
        : "=f"(c[0]), "=f"(c[1]), "=f"(c[2]), "=f"(c[3]) : "r"(a0), "r"(a1), "r"(a2), "r"(a3), "r"(b0), "r"(b1), "f"(0.f));
}
__device__ __forceinline__ void mma_bf16_k8_init(float (&c)[4], uint32_t a0, uint32_t a1, uint32_t b0) {
    asm("mma.sync.aligned.m16n8k8.row.col.f32.bf16.bf16.f32 {%0,%1,%2,%3}, {%4,%5}, {%6}, {%7,%7,%7,%7};"
        : "=f"(c[0]), "=f"(c[1]), "=f"(c[2]), "=f"(c[3]) : "r"(a0), "r"(a1), "r"(b0), "f"(0.f));
}
__device__ __forceinline__ uint32_t movm(uint32_t a) {
    uint32_t d; asm("movmatrix.sync.aligned.m8n8.trans.b16 %0, %1;" : "=r"(d) : "r"(a)); return d;
}
__device__ __forceinline__ void ldsm4(uint32_t (&r)[4], uint32_t a) {
    asm volatile("ldmatrix.sync.aligned.m8n8.x4.shared.b16 {%0,%1,%2,%3}, [%4];" : "=r"(r[0]), "=r"(r[1]), "=r"(r[2]), "=r"(r[3]) : "r"(a));
}
__device__ __forceinline__ void ldsm4t(uint32_t (&r)[4], uint32_t a) {
    asm volatile("ldmatrix.sync.aligned.m8n8.x4.trans.shared.b16 {%0,%1,%2,%3}, [%4];" : "=r"(r[0]), "=r"(r[1]), "=r"(r[2]), "=r"(r[3]) : "r"(a));
}
__device__ __forceinline__ void stsm4(uint32_t a, uint32_t r0, uint32_t r1, uint32_t r2, uint32_t r3) {
    asm volatile("stmatrix.sync.aligned.m8n8.x4.shared.b16 [%0], {%1,%2,%3,%4};" :: "r"(a), "r"(r0), "r"(r1), "r"(r2), "r"(r3) : "memory");
}
__device__ __forceinline__ uint4 lds128(uint32_t a) {
    uint4 v; asm volatile("ld.shared.v4.u32 {%0,%1,%2,%3}, [%4];" : "=r"(v.x), "=r"(v.y), "=r"(v.z), "=r"(v.w) : "r"(a)); return v;
}
__device__ __forceinline__ uint2 lds64(uint32_t a) {
    uint2 v; asm volatile("ld.shared.v2.u32 {%0,%1}, [%2];" : "=r"(v.x), "=r"(v.y) : "r"(a)); return v;
}
__device__ __forceinline__ uint32_t lds32(uint32_t a) {
    uint32_t v; asm volatile("ld.shared.u32 %0, [%1];" : "=r"(v) : "r"(a)); return v;
}
__device__ __forceinline__ uint32_t lds16(uint32_t a) {
    uint32_t v; asm volatile("ld.shared.u16 %0, [%1];" : "=r"(v) : "r"(a)); return v;
}
__device__ __forceinline__ void sts32(uint32_t a, uint32_t v) { asm volatile("st.shared.u32 [%0], %1;" :: "r"(a), "r"(v) : "memory"); }
__device__ __forceinline__ void sts64(uint32_t a, uint32_t x, uint32_t y) { asm volatile("st.shared.v2.u32 [%0], {%1,%2};" :: "r"(a), "r"(x), "r"(y) : "memory"); }
__device__ __forceinline__ uint32_t atoms_inc(uint32_t a) {
    uint32_t v; asm volatile("atom.shared.add.u32 %0, [%1], 1;" : "=r"(v) : "r"(a) : "memory"); return v;
}
__device__ __forceinline__ void cp16(uint32_t d, const void* s) {
    asm volatile("cp.async.cg.shared.global [%0], [%1], 16;" :: "r"(d), "l"(s) : "memory");
}
__device__ __forceinline__ void cp16z(uint32_t d, const void* s, uint32_t flag) {
    asm volatile("{.reg .pred p; setp.lt.s32 p, %2, 0; cp.async.cg.shared.global [%0], [%1], 16, p;}" :: "r"(d), "l"(s), "r"(flag) : "memory");
}
__device__ __forceinline__ void cp_commit() { asm volatile("cp.async.commit_group;" ::: "memory"); }
template <int n> __device__ __forceinline__ void cp_wait() { asm volatile("cp.async.wait_group %0;" :: "n"(n) : "memory"); }
__device__ __forceinline__ int4 ldg_stream(const int4* p) {
    int4 v; asm volatile("ld.global.nc.L1::no_allocate.v4.s32 {%0,%1,%2,%3}, [%4];" : "=r"(v.x), "=r"(v.y), "=r"(v.z), "=r"(v.w) : "l"(p)); return v;
}
__device__ __forceinline__ uint4 ldg_cg(const uint4* p) {
    uint4 v; asm volatile("ld.global.cg.v4.u32 {%0,%1,%2,%3}, [%4];" : "=r"(v.x), "=r"(v.y), "=r"(v.z), "=r"(v.w) : "l"(p) : "memory"); return v;
}
__device__ __forceinline__ uint32_t pack_bf16(float lo, float hi) {
    uint32_t d; asm("cvt.rn.bf16x2.f32 %0, %1, %2;" : "=r"(d) : "f"(hi), "f"(lo)); return d;
}
__device__ __forceinline__ uint32_t pack_f16(float lo, float hi) {
    uint32_t d; asm("cvt.rn.f16x2.f32 %0, %1, %2;" : "=r"(d) : "f"(hi), "f"(lo)); return d;
}
__device__ __forceinline__ uint32_t hmul2(uint32_t a, uint32_t b) { uint32_t d; asm("mul.rn.bf16x2 %0, %1, %2;" : "=r"(d) : "r"(a), "r"(b)); return d; }
__device__ __forceinline__ uint32_t hsub2(uint32_t a, uint32_t b) { uint32_t d; asm("sub.rn.bf16x2 %0, %1, %2;" : "=r"(d) : "r"(a), "r"(b)); return d; }
__device__ __forceinline__ uint32_t hadd2(uint32_t a, uint32_t b) { uint32_t d; asm("add.rn.bf16x2 %0, %1, %2;" : "=r"(d) : "r"(a), "r"(b)); return d; }
__device__ __forceinline__ uint32_t hfma2(uint32_t a, uint32_t b, uint32_t c) { uint32_t d; asm("fma.rn.bf16x2 %0, %1, %2, %3;" : "=r"(d) : "r"(a), "r"(b), "r"(c)); return d; }
__device__ __forceinline__ uint32_t shl_clamp(uint32_t a, uint32_t s) { uint32_t d; asm("shl.b32 %0, %1, %2;" : "=r"(d) : "r"(a), "r"(s)); return d; }
__device__ __forceinline__ float silu_half(float x) {
    float t; asm("tanh.approx.f32 %0, %1;" : "=f"(t) : "f"(x)); return fmaf(x, t, x);
}
template <int n> __device__ __forceinline__ uint32_t embed_bits(uint32_t w, uint32_t r) {
    int u = (int)(w & 0x7FFFu);
    int v = max(u - (int)r + (1 << (n - 1)), 0);
    v = (v & ~((1 << n) - 1)) | (int)r;
    return (w & 0xFFFF8000u) | (uint32_t)v;
}

__device__ __forceinline__ uint32_t make_table(uint32_t sb, int warp, int lane, int node0, int nvalid, float scale) {
    const int g = lane >> 2, t = lane & 3;
    float c[8][4];
#pragma unroll
    for (int j = 0; j < 8; j++) { c[j][0] = c[j][1] = c[j][2] = c[j][3] = 0.f; }
#pragma unroll
    for (int ks = 0; ks < 4; ks++) {
        uint32_t hf[4];
        const int r = lane & 15;
        ldsm4(hf, sb + SM_H + warp * 2048 + r * 128 + (((2 * ks + (lane >> 4)) ^ (r & 7)) << 4));
#pragma unroll
        for (int i = 0; i < 4; i++) {
            uint32_t w[4];
            const int k = 64 + 16 * ks + (lane & 7) + ((lane >> 4) << 3);
            ldsm4t(w, sb + SM_WE + k * 128 + (((2 * i + ((lane >> 3) & 1)) ^ (k & 7)) << 4));
            mma_bf16(c[2 * i], hf[0], hf[1], hf[2], hf[3], w[0], w[2]);
            mma_bf16(c[2 * i + 1], hf[0], hf[1], hf[2], hf[3], w[1], w[3]);
        }
    }
    float mx = 0.f;
#pragma unroll
    for (int u = 0; u < 2; u++) {
        uint32_t wd[8];
#pragma unroll
        for (int j = 0; j < 8; j++) {
            mx = fmaxf(mx, fmaxf(fabsf(c[j][2 * u]), fabsf(c[j][2 * u + 1])));
            wd[j] = pack_f16(c[j][2 * u] * scale, c[j][2 * u + 1] * scale);
        }
        const int r = g + 8 * u;
        if (t < 3) {
            const uint32_t p = lds16(sb + SM_POS + (warp * 16 + r) * 8 + 2 * t);
            wd[0] = embed_bits<3>(wd[0], p & 7);
            wd[1] = embed_bits<3>(wd[1], (p >> 3) & 7);
            wd[2] = embed_bits<3>(wd[2], (p >> 6) & 7);
            wd[3] = embed_bits<3>(wd[3], (p >> 9) & 7);
            wd[4] = embed_bits<2>(wd[4], (p >> 12) & 3);
            wd[5] = embed_bits<2>(wd[5], (p >> 14) & 3);
        }
        if (r < nvalid) {
            uint4* row = g_tab + (size_t)(node0 + r) * 8;
            row[t] = make_uint4(wd[0], wd[1], wd[2], wd[3]);
            row[t + 4] = make_uint4(wd[4], wd[5], wd[6], wd[7]);
        }
    }
    return __float_as_uint(mx * 0.5f);
}

__device__ __forceinline__ void load_we(uint32_t sb, const __nv_bfloat16* w_e, int tid) {
    for (int i = tid; i < 145 * 8; i += kThreads) {
        const int r = i >> 3, c = i & 7;
        cp16(sb + SM_WE + r * 128 + ((c ^ (r & 7)) << 4), (const uint4*)w_e + i);
    }
}

__global__ void __launch_bounds__(kThreads, 1)
egnn_kernel(const __nv_bfloat16* __restrict__ h, const __nv_bfloat16* __restrict__ pos,
            const __nv_bfloat16* __restrict__ e_attr, const int* __restrict__ src,
            const int* __restrict__ dst, const __nv_bfloat16* __restrict__ w_e,
            const __nv_bfloat16* __restrict__ w_x, const __nv_bfloat16* __restrict__ w_h,
            __nv_bfloat16* __restrict__ out_h, __nv_bfloat16* __restrict__ out_pos) {
    extern __shared__ __align__(128) unsigned char smem[];
    const uint32_t sb = (uint32_t)__cvta_generic_to_shared(smem);
    const int tid = threadIdx.x, warp = tid >> 5, lane = tid & 31;
    const int g = lane >> 2, t = lane & 3;
    const int cta = blockIdx.x;
    TSTAMP(0);

    const int e0 = cta * kChunk;
    const int ne4 = min(kChunk, kE - e0) >> 2;
    int4 dv[4], sv[4];
#pragma unroll
    for (int k = 0; k < 4; k++) {
        const int i = tid + k * kThreads;
        dv[k] = make_int4(0, 0, 0, 0);
        if (i < ne4) dv[k] = ldg_stream((const int4*)(dst + e0) + i);
    }
    const int nbase = cta * kNPC;
    const int ncta = min(kNPC, kN - nbase);
    const int node0 = nbase + warp * 16;
    const int nvalid = ncta - warp * 16;
#pragma unroll
    for (int j = 0; j < 4; j++) {
        const int r = j * 4 + (lane >> 3), c = lane & 7;
        const bool ok = r < nvalid;
        cp16z(sb + SM_H + warp * 2048 + r * 128 + ((c ^ (r & 7)) << 4), (const uint4*)h + (size_t)(ok ? node0 + r : 0) * 8 + c, ok ? 0u : ~0u);
    }
    load_we(sb, w_e, tid);
    cp_commit();
#pragma unroll
    for (int k = 0; k < 4; k++) {
        const int i = tid + k * kThreads;
        sv[k] = make_int4(0, 0, 0, 0);
        if (i < ne4) sv[k] = ldg_stream((const int4*)(src + e0) + i);
    }
    for (int i = tid; i < 128 * 8; i += kThreads) {
        const int r = i >> 3, c = i & 7;
        cp16(sb + SM_WH + r * 128 + ((c ^ (r & 7)) << 4), (const uint4*)w_h + i);
    }
    cp_commit();
    const unsigned epoch = g_epoch[cta] + 1;
    if (tid < 208) {
        uint32_t x = 0, y = 0, z = 0;
        if (tid < ncta) {
            const unsigned short* p = (const unsigned short*)pos + (size_t)(nbase + tid) * 3;
            x = p[0]; y = p[1]; z = p[2];
        }
        sts64(sb + SM_POS + tid * 8, x | (y << 16), z);
    } else if (tid < 208 + 160) {
        sts32(sb + SM_HIST + (tid - 208) * 4, 0);
    }
    if (tid < 32) sts32(sb + SM_WCNT + tid * 4, 0);
    if (tid < 8) sts32(sb + SM_MISC + tid * 4, 0);
    uint32_t wx[8];
#pragma unroll
    for (int j = 0; j < 8; j++) wx[j] = (uint32_t)((const unsigned short*)w_x)[8 * j + g] * 0x10001u;
    __syncthreads();

    uint32_t key[16];
#pragma unroll
    for (int k = 0; k < 4; k++) {
        const bool ok = tid + k * kThreads < ne4;
        const int d4[4] = {dv[k].x, dv[k].y, dv[k].z, dv[k].w};
#pragma unroll
        for (int q = 0; q < 4; q++) {
            const uint32_t bin = __umulhi((uint32_t)d4[q], kBinMul);
            const uint32_t dloc = (uint32_t)d4[q] - bin * kNPC;
            uint32_t rank = 0;
            if (ok) rank = atoms_inc(sb + SM_HIST + bin * 4);
            key[k * 4 + q] = bin | (rank << 8) | (dloc << 21);
        }
    }
    TSTAMP(1);
    cp_wait<1>();
    __syncthreads();
    if (tid == kThreads - 32) {
        asm volatile("cp.async.bulk.prefetch.L2.global [%0], %1;" :: "l"(e_attr + (size_t)e0 * 16), "r"(ne4 * 128) : "memory");
    }
    if (warp == 0) {
        uint32_t v[5], s = 0;
#pragma unroll
        for (int q = 0; q < 5; q++) { v[q] = lds32(sb + SM_HIST + (lane * 5 + q) * 4); s += v[q]; }
        uint32_t inc = s;
#pragma unroll
        for (int o = 1; o < 32; o <<= 1) { const uint32_t n = __shfl_up_sync(~0u, inc, o); if (lane >= o) inc += n; }
        uint32_t ex = inc - s;
#pragma unroll
        for (int q = 0; q < 5; q++) { sts32(sb + SM_OFF + (lane * 5 + q) * 4, ex); ex += v[q]; }
    }
    {
        uint32_t mx = make_table(sb, warp, lane, node0, nvalid, 0.5f * (float)(1 << kDefExp));
        mx = __reduce_max_sync(~0u, mx);
        if (lane == 0) asm volatile("red.shared.max.u32 [%0], %1;" :: "r"(sb + SM_MISC), "r"(mx) : "memory");
    }
    __syncthreads();
    TSTAMP(2);
#pragma unroll
    for (int k = 0; k < 4; k++) {
        const int i = tid + k * kThreads;
        const int s4[4] = {sv[k].x, sv[k].y, sv[k].z, sv[k].w};
        if (i < ne4) {
#pragma unroll
            for (int q = 0; q < 4; q++) {
                const uint32_t ky = key[k * 4 + q];
                const uint32_t p = lds32(sb + SM_OFF + (ky & 0xFF) * 4) + ((ky >> 8) & 0x1FFF);
                const uint32_t S = ((uint32_t)s4[q] << 7) | ((ky << 7) & 0x70000000u);
                const uint32_t Q = ((uint32_t)(e0 + i * 4 + q) << 5) | (ky >> 24);
                sts64(sb + SM_REC + p * 8, S, Q);
            }
        }
    }
    __syncthreads();
    TSTAMP(3);
#pragma unroll
    for (int k = 0; k < 8; k++) {
        const int i = tid + k * kThreads;
        if (i < ne4 * 2) g_rec[(e0 >> 1) + i] = lds128(sb + SM_REC + i * 16);
    }
    __syncthreads();
    if (tid < kG) {
        const uint32_t lo = lds32(sb + SM_OFF + tid * 4) | (lds32(sb + SM_HIST + tid * 4) << 13);
        const uint32_t hi = (epoch << 8) | (lds32(sb + SM_MISC) >> 23);
        asm volatile("fence.acq_rel.gpu;" ::: "memory");
        asm volatile("st.relaxed.gpu.global.u64 [%0], %1;" :: "l"(g_flag + tid * kG + cta), "l"(((unsigned long long)hi << 32) | lo) : "memory");
    }
    TSTAMP(4);

    uint32_t aw[4][2], aw2[4][2], wd[4][2], w3[4][4];
    {
        float c[2][4][4];
#pragma unroll
        for (int i = 0; i < 4; i++)
#pragma unroll
            for (int q = 0; q < 4; q++) c[0][i][q] = c[1][i][q] = 0.f;
#pragma unroll
        for (int ks = 0; ks < 4; ks++) {
            uint32_t hf[4];
            const int r = lane & 15;
            ldsm4(hf, sb + SM_H + warp * 2048 + r * 128 + (((2 * ks + (lane >> 4)) ^ (r & 7)) << 4));
#pragma unroll
            for (int i = 0; i < 4; i++) {
                uint32_t w[4];
                const int k = 16 * ks + (lane & 7) + ((lane >> 4) << 3);
                ldsm4t(w, sb + SM_WE + k * 128 + (((2 * i + ((lane >> 3) & 1)) ^ (k & 7)) << 4));
                mma_bf16(c[0][i], w[0], w[1], w[2], w[3], hf[0], hf[2]);
                mma_bf16(c[1][i], w[0], w[1], w[2], w[3], hf[1], hf[3]);
            }
        }
#pragma unroll
        for (int i = 0; i < 4; i++) {
            aw[i][0] = pack_bf16(0.5f * c[0][i][0], 0.5f * c[0][i][1]);
            aw[i][1] = pack_bf16(0.5f * c[0][i][2], 0.5f * c[0][i][3]);
            aw2[i][0] = pack_bf16(0.5f * c[1][i][0], 0.5f * c[1][i][1]);
            aw2[i][1] = pack_bf16(0.5f * c[1][i][2], 0.5f * c[1][i][3]);
            const int k = 129 + (lane & 7) + ((lane >> 4) << 3);
            ldsm4t(w3[i], sb + SM_WE + k * 128 + (((2 * i + ((lane >> 3) & 1)) ^ (k & 7)) << 4));
#pragma unroll
            for (int q = 0; q < 4; q++) w3[i][q] = hmul2(w3[i][q], 0x3F003F00u);
#pragma unroll
            for (int q = 0; q < 2; q++)
                wd[i][q] = hmul2(lds16(sb + SM_WE + 128 * 128 + (16 * i + 8 * q + g) * 2) * 0x10001u, 0x3F003F00u);
        }
    }

    uint32_t seg = 0;
    {
        uint32_t ex = 0;
        if (lane < kSegPerWarp) {
            const unsigned long long* fp = g_flag + cta * kG + warp * kSegPerWarp + lane;
            unsigned long long v;
            unsigned it = 0;
            do {
                asm volatile("ld.acquire.gpu.global.u64 %0, [%1];" : "=l"(v) : "l"(fp) : "memory");
                if (++it > kSpinLimit) __trap();
            } while ((uint32_t)(v >> 40) != (epoch & 0xFFFFFFu));
            seg = (uint32_t)v;
            ex = (uint32_t)(v >> 32) & 0xFF;
            sts32(sb + SM_SEG + (warp * kSegPerWarp + lane) * 4, seg);
        }
        __syncwarp();
        ex = __reduce_max_sync(~0u, ex);
        if (lane == 0) asm volatile("red.shared.max.u32 [%0], %1;" :: "r"(sb + SM_MISC + 4), "r"(ex) : "memory");
    }
    TSTAMP(5);
    auto place = [&](uint32_t S, uint32_t Q) {
        const uint32_t win = Q & 31;
        const uint32_t rank = atoms_inc(sb + SM_WCNT + win * 4);
        if (rank < kCapW) {
            const uint32_t idx = (win >> 1) * (2 * kCapW) + kCapW + (rank ^ ((win & 1) - 1));
            sts32(sb + SM_LS + idx * 4, S);
            sts32(sb + SM_LQ + idx * 4, Q);
        }
    };
    {
        uint4 rv[kSegPerWarp];
#pragma unroll
        for (int s = 0; s < kSegPerWarp; s++) {
            const uint32_t sg = __shfl_sync(~0u, seg, s);
            const uint32_t st = sg & 0x1FFF, en = st + (sg >> 13);
            const uint32_t pi = (st >> 1) + lane;
            rv[s] = make_uint4(0, 0, 0, 0);
            if (pi * 2 < en) rv[s] = ldg_cg(g_rec + (warp * kSegPerWarp + s) * (kChunk / 2) + pi);
        }
        bool more = false;
#pragma unroll
        for (int s = 0; s < kSegPerWarp; s++) {
            const uint32_t sg = __shfl_sync(~0u, seg, s);
            const uint32_t st = sg & 0x1FFF, en = st + (sg >> 13);
            const uint32_t p0 = (st & ~1u) + 2 * lane;
            if (p0 >= st && p0 < en) place(rv[s].x, rv[s].y);
            if (p0 + 1 < en) place(rv[s].z, rv[s].w);
            more |= (st & ~1u) + 64 < en;
        }
        if (more) {
            for (int s = 0; s < kSegPerWarp; s++) {
                const uint32_t sg = __shfl_sync(~0u, seg, s);
                const uint32_t st = sg & 0x1FFF, en = st + (sg >> 13);
                for (uint32_t p0 = (st & ~1u) + 64 + 2 * lane; p0 < en; p0 += 64) {
                    const uint4 v = ldg_cg(g_rec + (warp * kSegPerWarp + s) * (kChunk / 2) + (p0 >> 1));
                    place(v.x, v.y);
                    if (p0 + 1 < en) place(v.z, v.w);
                }
            }
        }
    }
    cp_wait<0>();
    __syncthreads();
    TSTAMP(6);

    int sexp = kDefExp;
    {
        const int ex = (int)lds32(sb + SM_MISC + 4) - 127;
        if (ex + kDefExp > 14 || (ex + kDefExp < -2 && ex != -127)) {
            sexp = min(max(10 - ex, -15), 24);
            make_table(sb, warp, lane, node0, nvalid, __uint_as_float((uint32_t)(126 + sexp) << 23));
            __syncthreads();
            if (tid < kG) {
                asm volatile("fence.acq_rel.gpu;" ::: "memory");
                asm volatile("st.relaxed.gpu.global.u32 [%0], %1;" :: "l"(g_flag2 + tid * kG + cta), "r"(epoch) : "memory");
                unsigned v, it = 0;
                do {
                    asm volatile("ld.acquire.gpu.global.u32 %0, [%1];" : "=r"(v) : "l"(g_flag2 + cta * kG + tid) : "memory");
                    if (++it > kSpinLimit) __trap();
                } while (v != epoch);
            }
            __syncthreads();
        }
    }
    const uint32_t one16 = sexp <= 14 ? (uint32_t)(15 - sexp) << 10 : 1u << (24 - sexp);
    const uint32_t ident = (g == 2 * t ? one16 : 0u) | (g == 2 * t + 1 ? one16 << 16 : 0u);

    const uint2 cnt = lds64(sb + SM_WCNT + warp * 8);
    const bool ovf = cnt.x > kCapW || cnt.y > kCapW;
    const uint32_t lsb = sb + SM_LS + warp * (2 * kCapW * 4);
    const uint32_t stb = sb + SM_STAGE + warp * (kStages * kStageBytes);
    const uint32_t cpB = (lane >> 3) * 512;
    const uint32_t cpE = 2048 + ((lane ^ ((lane >> 3) & 1)) << 4);
    const uint32_t ldQ = (SM_LQ - SM_LS) + ((lane & 14) + (lane >> 4)) * 4;
    const uint32_t ldB = g * 256 + ((t ^ ((g & 1) << 2)) << 4);
    const uint32_t ldE = 2048 + ((lane & 7) + ((lane >> 4) << 3)) * 32 + ((((lane >> 3) ^ (lane >> 2)) & 1) << 4);
    const uint32_t mlo = t < 3 ? 0x0000FFFFu : 0u, mhi = t < 3 ? 0xFFFF0000u : 0u;
    const uint32_t mev = (g & 1) ? 0u : ~0u;
    uint32_t pdb = sb + SM_POS + warp * 128 + 2 * t;
    float acc[4][4], accp[4];
    uint32_t m0[4][2];
    float p0a = 0.f, p0b = 0.f;
#pragma unroll
    for (int i = 0; i < 4; i++) { acc[i][0] = acc[i][1] = acc[i][2] = acc[i][3] = 0.f; accp[i] = 0.f; m0[i][0] = m0[i][1] = 0; }
    auto switch_window = [&]() {
#pragma unroll
        for (int i = 0; i < 4; i++) {
            m0[i][0] = pack_bf16(acc[i][0], acc[i][1]);
            m0[i][1] = pack_bf16(acc[i][2], acc[i][3]);
            acc[i][0] = acc[i][1] = acc[i][2] = acc[i][3] = 0.f;
            aw[i][0] = aw2[i][0]; aw[i][1] = aw2[i][1];
        }
        p0a = accp[0]; p0b = accp[1];
        accp[0] = accp[1] = accp[2] = accp[3] = 0.f;
        pdb += 64;
    };
    const char* tabp = (const char*)g_tab;
    const char* eap = (const char*)e_attr;
    auto issue = [&](uint32_t lp, uint32_t st) {
        const uint4 s4 = lds128(lp + (lane >> 3) * 16);
        const uint32_t q = lds32(lp + ldQ);
        const uint32_t c = (lane & 7) << 4;
        cp16z(st + cpB + c, tabp + ((s4.x & 0x3FFF80u) | c), s4.x);
        cp16z(st + cpB + 128 + c, tabp + ((s4.y & 0x3FFF80u) | c), s4.y);
        cp16z(st + cpB + 256 + (c ^ 64), tabp + ((s4.z & 0x3FFF80u) | c), s4.z);
        cp16z(st + cpB + 384 + (c ^ 64), tabp + ((s4.w & 0x3FFF80u) | c), s4.w);
        cp16z(st + cpE, eap + ((q & 0x7FFFFFE0u) | ((lane & 1) << 4)), q);
    };
    int cur_win = 0, cur_seg = 0, cur_pos = 0;
    for (;;) {
        int first, nt, sw;
        bool last;
        if (!ovf) {
            const int n0 = (cnt.x + 15) >> 4, n1 = (cnt.y + 15) >> 4;
            if (lane < 16) {
                const int i = kCapW - 1 - (int)cnt.x - lane;
                if (i >= kCapW - 16 * n0) { sts32(lsb + i * 4, 0x80000000u); sts32(lsb + (SM_LQ - SM_LS) + i * 4, 0x80000000u); }
            } else {
                const int i = kCapW + (int)cnt.y + lane - 16;
                if (i < kCapW + 16 * n1) { sts32(lsb + i * 4, 0x80000000u); sts32(lsb + (SM_LQ - SM_LS) + i * 4, 0x80000000u); }
            }
            first = kCapW - 16 * n0; nt = n0 + n1; sw = n0; last = true;
        } else {
            int n = 0;
            while (cur_seg < kG && n <= 2 * kCapW - 48) {
                const uint32_t sg = lds32(sb + SM_SEG + cur_seg * 4);
                const int st = sg & 0x1FFF, len = sg >> 13;
                uint2 v = make_uint2(0, 31);
                if (cur_pos + lane < len) v = __ldcg((const uint2*)g_rec + cur_seg * kChunk + st + cur_pos + lane);
                const bool hit = (int)(v.y & 31) == warp * 2 + cur_win;
                const uint32_t bal = __ballot_sync(~0u, hit);
                if (hit) {
                    const int i = n + __popc(bal & ((1u << lane) - 1));
                    sts32(lsb + i * 4, v.x); sts32(lsb + (SM_LQ - SM_LS) + i * 4, v.y);
                }
                n += __popc(bal);
                cur_pos += 32;
                if (cur_pos >= len) { cur_pos = 0; cur_seg++; }
            }
            if (lane < 16) { sts32(lsb + (n + lane) * 4, 0x80000000u); sts32(lsb + (SM_LQ - SM_LS) + (n + lane) * 4, 0x80000000u); }
            first = 0; nt = (n + 15) >> 4; sw = -1; last = false;
            if (cur_seg == kG) {
                if (cur_win == 0) { sw = nt; cur_win = 1; cur_seg = 0; } else last = true;
            }
        }
        __syncwarp();
        uint32_t lp = lsb + first * 4;
        uint32_t sc = stb, si = stb + 2 * kStageBytes;
        if (nt > 0) issue(lp, stb);
        cp_commit();
        if (nt > 1) issue(lp + 64, stb + kStageBytes);
        cp_commit();
#pragma unroll 1
        for (int it = 0; it < nt; it++) {
            if (it == sw) switch_window();
            if (it + 2 < nt) issue(lp + 128, si);
            cp_commit();
            const uint2 sg = lds64(lp + g * 8);
            const uint32_t pd = __byte_perm(lds16(pdb + (sg.x >> 25)), lds16(pdb + (sg.y >> 25)), 0x5410);
            const uint32_t oh0 = shl_clamp(0x3F80u, (sg.x >> 24) - 32 * t);
            const uint32_t oh1 = shl_clamp(0x3F80u, (sg.y >> 24) - 32 * t);
            const uint32_t s0 = movm(oh0), s1 = movm(oh1);
            cp_wait<2>();
            __syncwarp();
            uint32_t b[2][8], ef[4];
#pragma unroll
            for (int u = 0; u < 2; u++) {
                const uint4 x = lds128(sc + ldB + u * 128), y = lds128(sc + (ldB ^ 64) + u * 128);
                b[u][0] = x.x; b[u][1] = x.y; b[u][2] = x.z; b[u][3] = x.w;
                b[u][4] = y.x; b[u][5] = y.y; b[u][6] = y.z; b[u][7] = y.w;
            }
            ldsm4(ef, sc + ldE);
            uint32_t px[2];
#pragma unroll
            for (int u = 0; u < 2; u++) {
                uint32_t x = b[u][0] << 29;
                x = __funnelshift_r(x, b[u][1], 3);
                x = __funnelshift_r(x, b[u][2], 3);
                x = __funnelshift_r(x, b[u][3], 3);
                x = __funnelshift_r(x, b[u][4], 2);
                px[u] = __funnelshift_r(x, b[u][5], 2);
            }
            const uint32_t df = hsub2(pd, __byte_perm(px[0], px[1], 0x7632));
            const uint32_t sq = hmul2(df, df);
            const uint32_t q0 = sq & mlo, q1 = sq & mhi;
            uint32_t pa = 0, pb = 0;
#pragma unroll
            for (int i = 0; i < 4; i++) {
                float c0[4], c1[4];
                mma_f16_init(c0, ident, 0u, 0u, ident, b[0][2 * i], b[0][2 * i + 1]);
                mma_f16_init(c1, ident, 0u, 0u, ident, b[1][2 * i], b[1][2 * i + 1]);
                mma_bf16(c0, w3[i][0], w3[i][1], w3[i][2], w3[i][3], ef[0], ef[1]);
                mma_bf16(c1, w3[i][0], w3[i][1], w3[i][2], w3[i][3], ef[2], ef[3]);
                mma_bf16(c0, aw[i][0], aw[i][1], wd[i][0], wd[i][1], oh0, q0);
                mma_bf16(c1, aw[i][0], aw[i][1], wd[i][0], wd[i][1], oh1, q1);
                const uint32_t a0 = pack_bf16(silu_half(c0[0]), silu_half(c0[1]));
                const uint32_t a1 = pack_bf16(silu_half(c0[2]), silu_half(c0[3]));
                const uint32_t a2 = pack_bf16(silu_half(c1[0]), silu_half(c1[1]));
                const uint32_t a3 = pack_bf16(silu_half(c1[2]), silu_half(c1[3]));
                mma_bf16(acc[i], a0, a1, a2, a3, s0, s1);
                pa = i ? hfma2(a0, wx[2 * i], pa) : hmul2(a0, wx[0]);
                pb = i ? hfma2(a2, wx[2 * i], pb) : hmul2(a2, wx[0]);
                pa = hfma2(a1, wx[2 * i + 1], pa);
                pb = hfma2(a3, wx[2 * i + 1], pb);
            }
            float cs[4];
            mma_bf16_k8_init(cs, movm(pa), movm(pb), 0x3F803F80u);
            const uint32_t vt = movm(hmul2(df, pack_bf16(cs[0], cs[2])));
            mma_bf16(accp, vt & mev, 0u, vt & ~mev, 0u, s0, s1);
            lp += 64;
            si = sc;
            sc = (sc == stb + 2 * kStageBytes) ? stb : sc + kStageBytes;
        }
        if (sw == nt) switch_window();
        if (last) break;
        __syncwarp();
    }
    TSTAMP(7);

    {
        float c[8][4];
#pragma unroll
        for (int j = 0; j < 8; j++) { c[j][0] = c[j][1] = c[j][2] = c[j][3] = 0.f; }
        uint32_t hf[4][4];
#pragma unroll
        for (int ks = 0; ks < 8; ks++) {
            uint32_t a[4];
            if (ks < 4) {
                const int r = lane & 15;
                ldsm4(hf[ks], sb + SM_H + warp * 2048 + r * 128 + (((2 * ks + (lane >> 4)) ^ (r & 7)) << 4));
                a[0] = hf[ks][0]; a[1] = hf[ks][1]; a[2] = hf[ks][2]; a[3] = hf[ks][3];
            } else {
                const int i = ks - 4;
                a[0] = movm(m0[i][0]);
                a[1] = movm(pack_bf16(acc[i][0], acc[i][1]));
                a[2] = movm(m0[i][1]);
                a[3] = movm(pack_bf16(acc[i][2], acc[i][3]));
            }
#pragma unroll
            for (int i = 0; i < 4; i++) {
                uint32_t w[4];
                const int k = 16 * ks + (lane & 7) + ((lane >> 4) << 3);
                ldsm4t(w, sb + SM_WH + k * 128 + (((2 * i + ((lane >> 3) & 1)) ^ (k & 7)) << 4));
                mma_bf16(c[2 * i], a[0], a[1], a[2], a[3], w[0], w[2]);
                mma_bf16(c[2 * i + 1], a[0], a[1], a[2], a[3], w[1], w[3]);
            }
        }
        __syncwarp();
#pragma unroll
        for (int ks = 0; ks < 4; ks++) {
            uint32_t o[4];
#pragma unroll
            for (int q = 0; q < 4; q++) {
                const float* cc = c[2 * ks + (q >> 1)] + 2 * (q & 1);
                o[q] = hadd2(hf[ks][q], pack_bf16(silu_half(0.5f * cc[0]), silu_half(0.5f * cc[1])));
            }
            const int r = lane & 15;
            stsm4(sb + SM_H + warp * 2048 + r * 128 + (((2 * ks + (lane >> 4)) ^ (r & 7)) << 4), o[0], o[1], o[2], o[3]);
        }
        __syncwarp();
#pragma unroll
        for (int j = 0; j < 4; j++) {
            const int r = j * 4 + (lane >> 3), cc = lane & 7;
            const uint4 v = lds128(sb + SM_H + warp * 2048 + r * 128 + ((cc ^ (r & 7)) << 4));
            if (r < nvalid) ((uint4*)out_h)[(size_t)(node0 + r) * 8 + cc] = v;
        }
        const float s0a = p0a + __shfl_xor_sync(~0u, p0a, 4), s0b = p0b + __shfl_xor_sync(~0u, p0b, 4);
        const float s1a = accp[0] + __shfl_xor_sync(~0u, accp[0], 4), s1b = accp[1] + __shfl_xor_sync(~0u, accp[1], 4);
        if (g < 6) {
            const int cc = g >> 1, r = 2 * t + (g & 1);
            const uint32_t dl = pack_bf16((g & 1) ? s0b : s0a, (g & 1) ? s1b : s1a);
            const uint32_t pa = sb + SM_POS + (warp * 16 + r) * 8 + 2 * cc;
            const uint32_t o = hadd2(lds16(pa) | (lds16(pa + 64) << 16), dl);
            unsigned short* op = (unsigned short*)out_pos + (size_t)(node0 + r) * 3 + cc;
            if (r < nvalid) op[0] = (unsigned short)o;
            if (r + 8 < nvalid) op[24] = (unsigned short)(o >> 16);
        }
    }
    if (tid == 0) g_epoch[cta] = epoch;
    TSTAMP(8);
}

}

extern "C" void kernel_launch(void* const* d_in, const int* in_sizes, int n_in, void* d_out, int out_size) {
    static bool init = false;
    if (!init) {
        cudaFuncSetAttribute(egnn_kernel, cudaFuncAttributeMaxDynamicSharedMemorySize, SM_TOTAL);
        init = true;
    }
    __nv_bfloat16* out = (__nv_bfloat16*)d_out;
    egnn_kernel<<<kG, kThreads, SM_TOTAL>>>(
        (const __nv_bfloat16*)d_in[0], (const __nv_bfloat16*)d_in[1], (const __nv_bfloat16*)d_in[2],
        (const int*)d_in[3], (const int*)d_in[4], (const __nv_bfloat16*)d_in[5],
        (const __nv_bfloat16*)d_in[6], (const __nv_bfloat16*)d_in[7], out, out + (size_t)kN * 64);
}
```

```cpp
#include <cuda_runtime.h>
#include <cuda_bf16.h>
#include <cuda_fp16.h>
#include <stdint.h>

namespace {

constexpr int kN = 25000;
constexpr int kE = 800000;
constexpr int kG = 132;
constexpr int kNPC = 190;
constexpr int kChunk = 6064;
constexpr int kThreads = 512;
constexpr int kWarps = 16;
constexpr int kCapW = 272;
constexpr int kStageBytes = 2560;
constexpr int kSegPerWarp = (kG + kWarps - 1) / kWarps;
constexpr uint32_t kBinMul = 22605092u;
constexpr int kDefExp = 4;
constexpr unsigned kSpinLimit = 1u << 22;
constexpr uint32_t kPadQ = 6u << 28;

constexpr int SM_STAGE = 0;
constexpr int SM_REC = SM_STAGE;
constexpr int SM_WE = SM_STAGE + kG * 512;
constexpr int SM_H = SM_WE + 145 * 128;
constexpr int SM_LS = SM_STAGE + kWarps * 3 * kStageBytes;
constexpr int kLQ = kWarps * 2 * kCapW * 4;
constexpr int SM_WH = SM_LS + 2 * kLQ;
constexpr int SM_POS = SM_WH + 16384;
constexpr int SM_OH = SM_POS + 8192;
constexpr int SM_WX = SM_OH + 512;
constexpr int SM_HIST = SM_WX + 128;
constexpr int SM_WCNT = SM_HIST + 144 * 4;
constexpr int SM_MISC = SM_WCNT + 32 * 4;
constexpr int SM_CUR = SM_MISC + 32;
constexpr int SM_SEG = SM_CUR + 64;
constexpr int SM_TOTAL = SM_SEG + 144 * 4;
static_assert(SM_H + kWarps * 1536 <= SM_LS, "phase 1 aliasing");
static_assert(SM_TOTAL <= 232448, "shared memory");

__device__ uint4 g_tab[kG * kNPC * 8];
__device__ uint4 g_rec[kG * kG * 32];
__device__ uint4 g_ovf[kG * kChunk];
__device__ unsigned g_flag[2][160];
__device__ unsigned g_epoch[kG];
#define TDEP(i, x)
#define TSTAMP(i)

__device__ __forceinline__ void mma_bf16(float (&c)[4], uint32_t a0, uint32_t a1, uint32_t a2, uint32_t a3, uint32_t b0, uint32_t b1) {
    asm volatile("mma.sync.aligned.m16n8k16.row.col.f32.bf16.bf16.f32 {%0,%1,%2,%3}, {%4,%5,%6,%7}, {%8,%9}, {%0,%1,%2,%3};"
        : "+f"(c[0]), "+f"(c[1]), "+f"(c[2]), "+f"(c[3]) : "r"(a0), "r"(a1), "r"(a2), "r"(a3), "r"(b0), "r"(b1));
}
__device__ __forceinline__ void mma_f16_init(float (&c)[4], uint32_t a0, uint32_t a1, uint32_t a2, uint32_t a3, uint32_t b0, uint32_t b1) {
    asm volatile("mma.sync.aligned.m16n8k16.row.col.f32.f16.f16.f32 {%0,%1,%2,%3}, {%4,%5,%6,%7}, {%8,%9}, {%10,%10,%10,%10};"
        : "=f"(c[0]), "=f"(c[1]), "=f"(c[2]), "=f"(c[3]) : "r"(a0), "r"(a1), "r"(a2), "r"(a3), "r"(b0), "r"(b1), "f"(0.f));
}
__device__ __forceinline__ void mma_bf16_k8_init(float (&c)[4], uint32_t a0, uint32_t a1, uint32_t b0) {
    asm volatile("mma.sync.aligned.m16n8k8.row.col.f32.bf16.bf16.f32 {%0,%1,%2,%3}, {%4,%5}, {%6}, {%7,%7,%7,%7};"
        : "=f"(c[0]), "=f"(c[1]), "=f"(c[2]), "=f"(c[3]) : "r"(a0), "r"(a1), "r"(b0), "f"(0.f));
}
__device__ __forceinline__ uint32_t movm(uint32_t a) {
    uint32_t d; asm("movmatrix.sync.aligned.m8n8.trans.b16 %0, %1;" : "=r"(d) : "r"(a)); return d;
}
__device__ __forceinline__ void ldsm4(uint32_t (&r)[4], uint32_t a) {
    asm volatile("ldmatrix.sync.aligned.m8n8.x4.shared.b16 {%0,%1,%2,%3}, [%4];" : "=r"(r[0]), "=r"(r[1]), "=r"(r[2]), "=r"(r[3]) : "r"(a));
}
__device__ __forceinline__ void ldsm4t(uint32_t (&r)[4], uint32_t a) {
    asm volatile("ldmatrix.sync.aligned.m8n8.x4.trans.shared.b16 {%0,%1,%2,%3}, [%4];" : "=r"(r[0]), "=r"(r[1]), "=r"(r[2]), "=r"(r[3]) : "r"(a));
}
__device__ __forceinline__ void stsm4(uint32_t a, uint32_t r0, uint32_t r1, uint32_t r2, uint32_t r3) {
    asm volatile("stmatrix.sync.aligned.m8n8.x4.shared.b16 [%0], {%1,%2,%3,%4};" :: "r"(a), "r"(r0), "r"(r1), "r"(r2), "r"(r3) : "memory");
}
__device__ __forceinline__ uint4 lds128(uint32_t a) {
    uint4 v; asm volatile("ld.shared.v4.u32 {%0,%1,%2,%3}, [%4];" : "=r"(v.x), "=r"(v.y), "=r"(v.z), "=r"(v.w) : "r"(a)); return v;
}
__device__ __forceinline__ uint4 lds128v(uint32_t a) {
    uint4 v; asm volatile("ld.volatile.shared.v4.u32 {%0,%1,%2,%3}, [%4];" : "=r"(v.x), "=r"(v.y), "=r"(v.z), "=r"(v.w) : "r"(a) : "memory"); return v;
}
__device__ __forceinline__ uint2 lds64(uint32_t a) {
    uint2 v; asm volatile("ld.shared.v2.u32 {%0,%1}, [%2];" : "=r"(v.x), "=r"(v.y) : "r"(a)); return v;
}
__device__ __forceinline__ uint32_t lds32(uint32_t a) {
    uint32_t v; asm volatile("ld.shared.u32 %0, [%1];" : "=r"(v) : "r"(a)); return v;
}
__device__ __forceinline__ uint32_t lds16(uint32_t a) {
    uint32_t v; asm volatile("ld.shared.u16 %0, [%1];" : "=r"(v) : "r"(a)); return v;
}
__device__ __forceinline__ void sts32(uint32_t a, uint32_t v) { asm volatile("st.shared.u32 [%0], %1;" :: "r"(a), "r"(v) : "memory"); }
__device__ __forceinline__ void sts64(uint32_t a, uint32_t x, uint32_t y) { asm volatile("st.shared.v2.u32 [%0], {%1,%2};" :: "r"(a), "r"(x), "r"(y) : "memory"); }
__device__ __forceinline__ uint32_t atoms_inc(uint32_t a) {
    uint32_t v; asm volatile("atom.shared.add.u32 %0, [%1], 1;" : "=r"(v) : "r"(a) : "memory"); return v;
}
__device__ __forceinline__ void cp16(uint32_t d, const void* s) {
    asm volatile("cp.async.cg.shared.global [%0], [%1], 16;" :: "r"(d), "l"(s) : "memory");
}
__device__ __forceinline__ void cp16z(uint32_t d, const void* s, uint32_t flag) {
    asm volatile("{.reg .pred p; setp.lt.s32 p, %2, 0; cp.async.cg.shared.global [%0], [%1], 16, p;}" :: "r"(d), "l"(s), "r"(flag) : "memory");
}
__device__ __forceinline__ void cp_commit() { asm volatile("cp.async.commit_group;" ::: "memory"); }
template <int n> __device__ __forceinline__ void cp_wait() { asm volatile("cp.async.wait_group %0;" :: "n"(n) : "memory"); }
__device__ __forceinline__ int4 ldg_stream(const int4* p) {
    int4 v; asm volatile("ld.relaxed.gpu.global.v4.s32 {%0,%1,%2,%3}, [%4];" : "=r"(v.x), "=r"(v.y), "=r"(v.z), "=r"(v.w) : "l"(p) : "memory"); return v;
}
__device__ __forceinline__ uint32_t ldg16(const unsigned short* p) {
    uint32_t v; asm volatile("ld.relaxed.gpu.global.u16 %0, [%1];" : "=r"(v) : "l"(p) : "memory"); return v;
}
__device__ __forceinline__ uint4 ldg_cg(const uint4* p) {
    uint4 v; asm volatile("ld.global.cg.v4.u32 {%0,%1,%2,%3}, [%4];" : "=r"(v.x), "=r"(v.y), "=r"(v.z), "=r"(v.w) : "l"(p) : "memory"); return v;
}
__device__ __forceinline__ uint32_t pack_bf16(float lo, float hi) {
    uint32_t d; asm("cvt.rn.bf16x2.f32 %0, %1, %2;" : "=r"(d) : "f"(hi), "f"(lo)); return d;
}
__device__ __forceinline__ uint32_t pack_f16(float lo, float hi) {
    uint32_t d; asm("cvt.rn.f16x2.f32 %0, %1, %2;" : "=r"(d) : "f"(hi), "f"(lo)); return d;
}
__device__ __forceinline__ uint32_t hmul2(uint32_t a, uint32_t b) { uint32_t d; asm("mul.rn.bf16x2 %0, %1, %2;" : "=r"(d) : "r"(a), "r"(b)); return d; }
__device__ __forceinline__ uint32_t hsub2(uint32_t a, uint32_t b) { uint32_t d; asm("sub.rn.bf16x2 %0, %1, %2;" : "=r"(d) : "r"(a), "r"(b)); return d; }
__device__ __forceinline__ uint32_t hadd2(uint32_t a, uint32_t b) { uint32_t d; asm("add.rn.bf16x2 %0, %1, %2;" : "=r"(d) : "r"(a), "r"(b)); return d; }
__device__ __forceinline__ uint32_t hfma2(uint32_t a, uint32_t b, uint32_t c) { uint32_t d; asm("fma.rn.bf16x2 %0, %1, %2, %3;" : "=r"(d) : "r"(a), "r"(b), "r"(c)); return d; }
__device__ __forceinline__ uint32_t shl_clamp(uint32_t a, uint32_t s) { uint32_t d; asm("shl.b32 %0, %1, %2;" : "=r"(d) : "r"(a), "r"(s)); return d; }
__device__ __forceinline__ float silu_half(float x) {
    float t; asm volatile("tanh.approx.f32 %0, %1;" : "=f"(t) : "f"(x)); return fmaf(x, t, x);
}
__device__ __forceinline__ void ldsm2t(uint32_t& r0, uint32_t& r1, uint32_t a) {
    asm volatile("ldmatrix.sync.aligned.m8n8.x2.trans.shared.b16 {%0,%1}, [%2];" : "=r"(r0), "=r"(r1) : "r"(a));
}
__device__ __forceinline__ void sts128(uint32_t a, uint32_t x, uint32_t y, uint32_t z, uint32_t w) {
    asm volatile("st.shared.v4.u32 [%0], {%1,%2,%3,%4};" :: "r"(a), "r"(x), "r"(y), "r"(z), "r"(w) : "memory");
}
__device__ __forceinline__ void cp16p(uint32_t d, const void* s, bool p) {
    asm volatile("{.reg .pred p; setp.ne.u32 p, %2, 0; @p cp.async.cg.shared.global [%0], [%1], 16;}" :: "r"(d), "l"(s), "r"((uint32_t)p) : "memory");
}
template <int mul> __device__ __forceinline__ void cp16g(uint32_t d, uint64_t base, uint32_t idx, bool p) {
    asm volatile("{.reg .pred p; .reg .b64 a; setp.ne.u32 p, %3, 0; mul.wide.u32 a, %2, %4; add.s64 a, a, %1; @p cp.async.cg.shared.global [%0], [a], 16;}"
                 :: "r"(d), "l"(base), "r"(idx), "r"((uint32_t)p), "n"(mul) : "memory");
}
template <uint32_t m> __device__ __forceinline__ uint32_t bitsel(uint32_t a, uint32_t b) {
    uint32_t d; asm("lop3.b32 %0, %1, %2, %3, 0xE2;" : "=r"(d) : "r"(a), "n"(m), "r"(b)); return d;
}
__device__ __forceinline__ uint32_t hfma2_lo(uint32_t a, uint32_t b, uint32_t c) {
    uint32_t d; asm("{.reg .b16 l,h; .reg .b32 x; mov.b32 {l,h}, %2; mov.b32 x, {l,l}; fma.rn.bf16x2 %0, %1, x, %3;}" : "=r"(d) : "r"(a), "r"(b), "r"(c)); return d;
}
__device__ __forceinline__ uint32_t hfma2_hi(uint32_t a, uint32_t b, uint32_t c) {
    uint32_t d; asm("{.reg .b16 l,h; .reg .b32 x; mov.b32 {l,h}, %2; mov.b32 x, {h,h}; fma.rn.bf16x2 %0, %1, x, %3;}" : "=r"(d) : "r"(a), "r"(b), "r"(c)); return d;
}
__device__ __forceinline__ uint4 ld_relaxed(const uint4* p) {
    uint4 v; asm volatile("ld.relaxed.gpu.global.v4.u32 {%0,%1,%2,%3}, [%4];" : "=r"(v.x), "=r"(v.y), "=r"(v.z), "=r"(v.w) : "l"(p) : "memory"); return v;
}
__device__ __forceinline__ void st_relaxed(uint4* p, uint32_t x, uint32_t y, uint32_t z, uint32_t w) {
    asm volatile("st.relaxed.gpu.global.v4.u32 [%0], {%1,%2,%3,%4};" :: "l"(p), "r"(x), "r"(y), "r"(z), "r"(w) : "memory");
}
__device__ __forceinline__ uint32_t hmul2_lo(uint32_t a, uint32_t b) {
    uint32_t d; asm("{.reg .b16 l,h; .reg .b32 x; mov.b32 {l,h}, %2; mov.b32 x, {l,l}; mul.rn.bf16x2 %0, %1, x;}" : "=r"(d) : "r"(a), "r"(b)); return d;
}
__device__ __forceinline__ uint32_t hmul2_hi(uint32_t a, uint32_t b) {
    uint32_t d; asm("{.reg .b16 l,h; .reg .b32 x; mov.b32 {l,h}, %2; mov.b32 x, {h,h}; mul.rn.bf16x2 %0, %1, x;}" : "=r"(d) : "r"(a), "r"(b)); return d;
}
template <int n> __device__ __forceinline__ uint32_t embed_bits(uint32_t w, uint32_t r) {
    constexpr uint32_t m = ((1u << n) - 1) * 0x10001u;
    r &= m;
    const uint32_t v = __vmaxu2((w & 0x7FFF7FFFu) + (0x10001u << (n - 1)), r) - r;
    return (v & ~m) | r | (w & 0x80008000u);
}

__device__ __forceinline__ void load_hf(uint32_t (&hf)[4], uint32_t sb, int warp, int lane, int ks) {
    const int r = lane & 15, j = r < 8 ? r : 4 + (r >> 1);
    ldsm4(hf, sb + SM_H + warp * 1536 + j * 128 + (((2 * ks + (lane >> 4)) ^ (j & 7)) << 4));
}

template <class F>
__device__ __forceinline__ uint32_t make_table(uint32_t sb, int warp, int lane, int nbase, int ncta, float scale, F hook) {
    const int g = lane >> 2, t = lane & 3;
    float c[8][4];
#pragma unroll
    for (int j = 0; j < 8; j++) { c[j][0] = c[j][1] = c[j][2] = c[j][3] = 0.f; }
#pragma unroll
    for (int ks = 0; ks < 4; ks++) {
        uint32_t hf[4];
        load_hf(hf, sb, warp, lane, ks);
#pragma unroll
        for (int i = 0; i < 4; i++) {
            uint32_t w[4];
            const int k = 64 + 16 * ks + (lane & 7) + ((lane >> 4) << 3);
            ldsm4t(w, sb + SM_WE + k * 128 + (((2 * i + ((lane >> 3) & 1)) ^ (k & 7)) << 4));
            mma_bf16(c[2 * i], hf[0], hf[1], hf[2], hf[3], w[0], w[2]);
            mma_bf16(c[2 * i + 1], hf[0], hf[1], hf[2], hf[3], w[1], w[3]);
            hook(ks * 4 + i);
        }
    }
    float mx = 0.f;
#pragma unroll
    for (int u = 0; u < 2; u++) {
        uint32_t wd[8];
#pragma unroll
        for (int j = 0; j < 8; j++) {
            mx = fmaxf(mx, fmaxf(fabsf(c[j][2 * u]), fabsf(c[j][2 * u + 1])));
            wd[j] = pack_f16(c[j][2 * u] * scale, c[j][2 * u + 1] * scale);
        }
        const int j = u ? 8 + (g >> 1) : g;
        const int sub = j >= 6, hi = j - 6 * sub;
        const uint32_t p = __byte_perm(lds32(sb + SM_POS + warp * 512 + sub * 128 + hi * 16 + 4 * t), 0, 0x4342);
        wd[0] = embed_bits<3>(wd[0], p);
        wd[1] = embed_bits<3>(wd[1], p >> 3);
        wd[2] = embed_bits<2>(wd[2], p >> 6);
        const int dloc = warp + 16 * sub + 32 * hi;
        if (dloc < ncta) {
            uint4* row = g_tab + (size_t)(nbase + dloc) * 8;
            if (u == 0) {
                row[t] = make_uint4(wd[0], wd[1], wd[2], wd[3]);
                row[t + 4] = make_uint4(wd[4], wd[5], wd[6], wd[7]);
            } else {
                row[t + 4 * (g & 1)] = (g & 1) ? make_uint4(wd[4], wd[5], wd[6], wd[7]) : make_uint4(wd[0], wd[1], wd[2], wd[3]);
            }
        }
    }
    return __float_as_uint(mx * 0.5f);
}

#define FM 8
#define FENCE(k) do { if (FM >> k & 1) asm volatile("{.reg .pred p; setp.eq.u32 p, %0, " #k "; @p trap;}" :: "r"(oa) : "memory"); } while (0)
#define HD 0
#define SE 9
#define SD 2
#define RL 0
template <int N> struct IC { static constexpr int v = N; };

__global__ void __launch_bounds__(kThreads, 1)
egnn_kernel(const __nv_bfloat16* __restrict__ h, const __nv_bfloat16* __restrict__ pos,
            const __nv_bfloat16* __restrict__ e_attr, const int* __restrict__ src,
            const int* __restrict__ dst, const __nv_bfloat16* __restrict__ w_e,
            const __nv_bfloat16* __restrict__ w_x, const __nv_bfloat16* __restrict__ w_h,
            __nv_bfloat16* __restrict__ out_h, __nv_bfloat16* __restrict__ out_pos) {
    extern __shared__ __align__(128) unsigned char smem[];
    const uint32_t sb = (uint32_t)__cvta_generic_to_shared(smem);
    const int tid = threadIdx.x, warp = tid >> 5, lane = tid & 31;
    const int g = lane >> 2, t = lane & 3;
    const int cta = blockIdx.x;
    TSTAMP(0);

    const int e0 = cta * kChunk;
    const int ne4 = min(kChunk, kE - e0) >> 2;
    int4 dv[3], sv[3];
#pragma unroll
    for (int k = 0; k < 3; k++) dv[k] = ldg_stream((const int4*)(dst + e0) + min(tid + k * kThreads, ne4 - 1));
    unsigned epoch;
    asm volatile("ld.relaxed.gpu.global.u32 %0, [%1];" : "=r"(epoch) : "l"(g_epoch + cta) : "memory");
#pragma unroll
    for (int k = 0; k < 3; k++) sv[k] = ldg_stream((const int4*)(src + e0) + min(tid + k * kThreads, ne4 - 1));
    const int nbase = cta * kNPC;
    const int ncta = min(kNPC, kN - nbase);
    uint32_t px = 0, py = 0, pz = 0;
    {
        const int dloc = warp + 16 * (lane >> 3) + 32 * (lane & 7);
        if (lane < 16 && (lane & 7) < 6 && dloc < ncta) {
            const unsigned short* p = (const unsigned short*)pos + (size_t)(nbase + dloc) * 3;
            px = ldg16(p); py = ldg16(p + 1); pz = ldg16(p + 2);
        }
    }
#pragma unroll
    for (int k = 0; k < 9; k++) {
        const int i = tid + k * kThreads;
        if (i < kG * 32) sts128(sb + SM_REC + i * 16, 0u, 0u, 0u, 0u);
    }
    if (tid < 144 + 32 + 8 + 16) sts32(sb + SM_HIST + tid * 4, tid < 144 ? 1u : 0u);
    else if (tid >= 256 && tid < 384) {
        const int w = tid - 256, r = (w >> 2) & 7, j = w < 64 ? r + 6 * (w >> 5) : r;
        sts32(sb + SM_OH + w * 4, (r < 6 && (j >> 1) == (w & 3)) ? 0x3F80u << ((j & 1) * 16) : 0u);
    }
    __syncthreads();
#pragma unroll
    for (int q = 0; q < 3; q++) {
        const int i = tid + q * kThreads, r = i >> 3, c = i & 7;
        if (i < 145 * 8) cp16(sb + SM_WE + r * 128 + ((c ^ (r & 7)) << 4), (const uint4*)w_e + i);
    }
    if (tid >= kThreads - 8) cp16(sb + SM_WX + (tid & 7) * 16, (const uint4*)w_x + (tid & 7));
    cp_commit();
#pragma unroll
    for (int q = 0; q < 3; q++) {
        const int j = q * 4 + (lane >> 3), c = lane & 7;
        const int sub = j >= 6, dloc = warp + 16 * sub + 32 * (j - 6 * sub);
        const bool ok = dloc < ncta;
        cp16z(sb + SM_H + warp * 1536 + j * 128 + ((c ^ (j & 7)) << 4), (const uint4*)h + (size_t)(ok ? nbase + dloc : 0) * 8 + c, ok ? 0u : ~0u);
    }
    cp_commit();
    epoch += (epoch & 0xFFFFFFu) == 0xFFFFFFu ? 2 : 1;
    const uint32_t tag = epoch << 8;
    TDEP(11, dv[0].x);

#pragma unroll
    for (int k = 0; k < 3; k++) {
        const int i = tid + k * kThreads;
        const int d4[4] = {dv[k].x, dv[k].y, dv[k].z, dv[k].w};
        const int s4[4] = {sv[k].x, sv[k].y, sv[k].z, sv[k].w};
        if (k < 2 || i < ne4) {
            uint32_t bin[4], rank[4];
#pragma unroll
            for (int q = 0; q < 4; q++) {
                bin[q] = __umulhi((uint32_t)d4[q], kBinMul);
                rank[q] = atoms_inc(sb + SM_HIST + bin[q] * 4);
            }
#pragma unroll
            for (int q = 0; q < 4; q++) {
                const uint32_t w0 = (uint32_t)s4[q] + ((uint32_t)(i * 4 + q) << 15);
                const uint32_t w1 = (uint32_t)d4[q] + tag - bin[q] * kNPC;
                if (rank[q] < 64) sts64(sb + SM_REC + bin[q] * 512 + ((rank[q] ^ ((2 * bin[q]) & 14)) << 3), w0, w1);
            }
            if ((rank[0] | rank[1] | rank[2] | rank[3]) >= 64) {
#pragma unroll
                for (int q = 0; q < 4; q++) {
                    if (rank[q] >= 64) {
                        const uint32_t w1 = (uint32_t)d4[q] + tag - bin[q] * kNPC;
                        st_relaxed(g_ovf + cta * kChunk + atoms_inc(sb + SM_MISC + 8), (uint32_t)s4[q] + ((uint32_t)(i * 4 + q) << 15), w1, bin[q], w1);
                    }
                }
            }
        }
    }
    if (lane < 16) {
        const int j = 6 * (lane >> 3) + (lane & 7);
        const bool v = (lane & 7) < 6;
        sts128(sb + SM_POS + warp * 512 + lane * 16, (px << 16) | (v && j == 8 ? 0x3F80u : 0u), (py << 16) | (v && j == 9 ? 0x3F80u : 0u),
               (pz << 16) | (v && j == 10 ? 0x3F80u : 0u), v && j == 11 ? 0x3F80u : 0u);
    } else {
        const uint32_t o = 0x3F80u << ((lane & 1) * 16), r = (lane & 7) >> 1;
        sts128(sb + SM_POS + warp * 512 + lane * 16, r == 0 ? o : 0u, r == 1 ? o : 0u, r == 2 ? o : 0u, 0u);
    }
    TSTAMP(1);
    cp_wait<1>();
    __syncthreads();
    TDEP(14, lds32(sb + SM_HIST));
    {
        const int b = lane * kWarps + warp;
        if (b < kG) sts64(sb + SM_REC + b * 512 + ((b & 7) << 4), lds32(sb + SM_HIST + b * 4) | (lds32(sb + SM_MISC + 8) << 13), tag);
        __syncwarp();
        auto send = [&](int s) {
            if (s < kSegPerWarp - 1 || (s == kSegPerWarp - 1 && s * kWarps + warp < kG)) {
                const uint4 v = lds128(sb + SM_REC + s * (kWarps * 512) + tid * 16);
                st_relaxed(g_rec + cta * (kG * 32) + s * kThreads + tid, v.x, v.y, v.z, v.w);
            }
        };
#pragma unroll
        for (int s = 0; s < SE; s++) send(s);
        cp_wait<0>();
        __syncwarp();
        TSTAMP(12);
        uint32_t mx = make_table(sb, warp, lane, nbase, ncta, 0.5f * (float)(1 << kDefExp), [&](int step) { if (step % SD == 0) send(SE + step / SD); });
        mx = __reduce_max_sync(~0u, mx);
        if (lane == 0) asm volatile("red.shared.max.u32 [%0], %1;" :: "r"(sb + SM_MISC), "r"(mx) : "memory");
    }
    TSTAMP(13);
    if (warp != kWarps - 1) {
        asm volatile("bar.arrive 1, %0;" :: "n"(kThreads) : "memory");
    } else {
        asm volatile("bar.sync 1, %0;" :: "n"(kThreads) : "memory");
        if (lane == 0) {
            asm volatile("fence.acq_rel.gpu;" ::: "memory");
            asm volatile("st.relaxed.gpu.global.u32 [%0], %1;" :: "l"(g_flag[0] + cta), "r"(tag | (lds32(sb + SM_MISC) >> 23)) : "memory");
        }
        __syncwarp();
    }
    TSTAMP(2);
#pragma unroll
    for (int q = 0; q < 2; q++) {
        const int i = tid + q * kThreads, r = i >> 3, c = i & 7;
        cp16(sb + SM_WH + r * 128 + ((c ^ (r & 7)) << 4), (const uint4*)w_h + i);
    }
    cp_commit();

    uint32_t aw[4][4], w3[4][4];
    {
        float c[2][4][4];
#pragma unroll
        for (int i = 0; i < 4; i++)
#pragma unroll
            for (int q = 0; q < 4; q++) c[0][i][q] = c[1][i][q] = 0.f;
#pragma unroll
        for (int ks = 0; ks < 4; ks++) {
            uint32_t hf[4];
            load_hf(hf, sb, warp, lane, ks);
#pragma unroll
            for (int i = 0; i < 4; i++) {
                uint32_t w[4];
                const int k = 16 * ks + (lane & 7) + ((lane >> 4) << 3);
                ldsm4t(w, sb + SM_WE + k * 128 + (((2 * i + ((lane >> 3) & 1)) ^ (k & 7)) << 4));
                mma_bf16(c[0][i], w[0], w[1], w[2], w[3], hf[0], hf[2]);
                mma_bf16(c[1][i], w[0], w[1], w[2], w[3], hf[1], hf[3]);
            }
        }
#pragma unroll
        for (int i = 0; i < 4; i++) {
            aw[i][0] = pack_bf16(0.5f * c[0][i][0], 0.5f * c[0][i][1]);
            aw[i][1] = pack_bf16(0.5f * c[0][i][2], 0.5f * c[0][i][3]);
#pragma unroll
            for (int q = 0; q < 2; q++)
                aw[i][2 + q] = pack_bf16(0.5f * c[1][i][2 * q], 0.5f * __uint_as_float(lds16(sb + SM_WE + 128 * 128 + (16 * i + 8 * q + g) * 2) << 16));
        }
    }
    TSTAMP(4);
    const uint4* recp = g_rec + (warp * kG + cta) * 32 + (lane ^ (cta & 7));
    uint4 rv[kSegPerWarp];
#pragma unroll
    for (int s = 0; s < kSegPerWarp; s++) {
        rv[s] = make_uint4(0, tag, 0, tag);
        if (s < kSegPerWarp - 1 || s * kWarps + warp < kG) rv[s] = ld_relaxed(recp + s * (kWarps * kG * 32));
    }
    auto place = [&](uint32_t w0, uint32_t x, uint32_t ebase, uint32_t rank) {
        if (rank < kCapW) {
            const uint32_t a = sb + SM_LS + kCapW * 4 + (x & 15) * (2 * kCapW * 4) + (rank ^ (((x >> 4) & 1) - 1)) * 4;
            sts32(a, w0 & 0x7FFFu);
            sts32(a + kLQ, ((w0 >> 15) + ebase) | ((x << 23) & 0x70000000u));
        }
    };
    {
        unsigned spin = 0;
        uint32_t cnt[kSegPerWarp];
        for (;;) {
            bool bad = false;
#pragma unroll
            for (int s = 0; s < kSegPerWarp; s++) {
                cnt[s] = __shfl_sync(~0u, rv[s].x, 0) & 0x1FFF;
                const bool b0 = (rv[s].y ^ tag) >= 256 && (lane == 0 || 2 * lane < cnt[s]);
                const bool b1 = (rv[s].w ^ tag) >= 256 && 2 * lane + 1 < cnt[s];
                if (b0 || b1) {
                    rv[s] = ld_relaxed(recp + s * (kWarps * kG * 32));
                    bad = true;
                }
            }
            if (!__any_sync(~0u, bad)) break;
            if (++spin > kSpinLimit) __trap();
        }
        TSTAMP(9);
        int more = -1;
#pragma unroll
        for (int s = 0; s < kSegPerWarp; s++) {
            if (lane == 0) sts32(sb + SM_SEG + (s * kWarps + warp) * 4, rv[s].x);
            if (cnt[s] > 64) more = s * kWarps + warp;
        }
        uint4 ov = make_uint4(0, 0, 0, 0);
        if (more >= 0) ov = ld_relaxed(g_ovf + more * kChunk + lane);
        uint32_t rk[kSegPerWarp][2];
#pragma unroll
        for (int s = 0; s < kSegPerWarp; s++) {
            rk[s][0] = rk[s][1] = kCapW;
            if (lane != 0 && 2 * lane < cnt[s]) rk[s][0] = atoms_inc(sb + SM_WCNT + (rv[s].y & 31) * 4);
            if (2 * lane + 1 < cnt[s]) rk[s][1] = atoms_inc(sb + SM_WCNT + (rv[s].w & 31) * 4);
        }
#pragma unroll
        for (int s = 0; s < kSegPerWarp; s++) {
            place(rv[s].x, rv[s].y, (s * kWarps + warp) * kChunk, rk[s][0]);
            place(rv[s].z, rv[s].w, (s * kWarps + warp) * kChunk, rk[s][1]);
        }
        TSTAMP(5);
        __syncwarp();
        for (int b = more; b >= 0; b -= kWarps) {
            const uint32_t sg = lds32(sb + SM_SEG + b * 4);
            if ((sg & 0x1FFF) <= 64) continue;
            for (uint32_t i = lane; i < (sg >> 13); i += 32) {
                while (((ov.y ^ tag) | (ov.w ^ tag)) >= 256) {
                    ov = ld_relaxed(g_ovf + b * kChunk + i);
                    if (++spin > kSpinLimit) __trap();
                }
                if (ov.z == cta) place(ov.x, ov.y, b * kChunk, atoms_inc(sb + SM_WCNT + (ov.y & 31) * 4));
                ov.y = 0;
            }
            ov.y = 0;
        }
        TSTAMP(10);
        if (tid >= kThreads - kG) {
            uint32_t v;
            do {
                asm volatile("ld.acquire.gpu.global.u32 %0, [%1];" : "=r"(v) : "l"(g_flag[0] + (tid - (kThreads - kG))) : "memory");
                if (++spin > kSpinLimit) __trap();
            } while ((v ^ tag) >= 256);
            asm volatile("red.shared.max.u32 [%0], %1;" :: "r"(sb + SM_MISC + 4), "r"(v & 255) : "memory");
        }
    }
#pragma unroll
    for (int i = 0; i < 4; i++) {
        const int k = 129 + (lane & 7) + ((lane >> 4) << 3);
        ldsm4t(w3[i], sb + SM_WE + k * 128 + (((2 * i + ((lane >> 3) & 1)) ^ (k & 7)) << 4));
#pragma unroll
        for (int q = 0; q < 4; q++) w3[i][q] = hmul2(w3[i][q], 0x3F003F00u);
    }
    uint32_t wx[4];
#pragma unroll
    for (int j = 0; j < 4; j++) wx[j] = lds16(sb + SM_WX + (16 * j + g) * 2) | (lds16(sb + SM_WX + (16 * j + 8 + g) * 2) << 16);
    cp_wait<0>();
    __syncthreads();
    TSTAMP(6);

    int sexp = kDefExp;
    {
        const int ex = (int)lds32(sb + SM_MISC + 4) - 127;
        if (ex + kDefExp > 14 || (ex + kDefExp < -2 && ex != -127)) {
            sexp = min(max(10 - ex, -15), 24);
            make_table(sb, warp, lane, nbase, ncta, __uint_as_float((uint32_t)(126 + sexp) << 23), [](int) {});
            __syncthreads();
            if (tid == 0) {
                asm volatile("fence.acq_rel.gpu;" ::: "memory");
                asm volatile("st.relaxed.gpu.global.u32 [%0], %1;" :: "l"(g_flag[1] + cta), "r"(epoch) : "memory");
            }
            if (tid < kG) {
                unsigned v, it = 0;
                do {
                    asm volatile("ld.acquire.gpu.global.u32 %0, [%1];" : "=r"(v) : "l"(g_flag[1] + tid) : "memory");
                    if (++it > kSpinLimit) __trap();
                } while (v != epoch);
            }
            __syncthreads();
        }
    }
    const uint32_t one16 = sexp <= 14 ? (uint32_t)(15 - sexp) << 10 : 1u << (24 - sexp);
    const uint32_t ident = (g == 2 * t ? one16 : 0u) | (g == 2 * t + 1 ? one16 << 16 : 0u);

    const uint32_t lsb = sb + SM_LS + warp * (2 * kCapW * 4);
    const uint32_t stb = sb + SM_STAGE + warp * (3 * kStageBytes);
    const uint32_t cpB = stb + ((lane ^ ((lane >> 1) & 4)) << 4);
    const uint32_t ldB = stb + g * 128 + ((t ^ ((g & 1) << 2)) << 4);
    const uint32_t ldE = stb + 2048 + ((lane & 7) + ((lane >> 4) << 3)) * 32 + ((((lane >> 3) ^ (lane >> 2)) & 1) << 4);
    uint32_t ohb = (lane & 8) ? sb + SM_POS + warp * 512 : sb + SM_OH;
    uint64_t tabp = (uint64_t)__cvta_generic_to_global(g_tab) + ((lane & 7) << 4);
    uint64_t eap = (uint64_t)__cvta_generic_to_global(e_attr) + (((lane ^ (lane >> 3)) & 1) << 4);
    sts128(stb + 1024 + lane * 16, (uint32_t)tabp, (uint32_t)(tabp >> 32), (uint32_t)eap, (uint32_t)(eap >> 32));
    asm volatile("ld.volatile.shared.v2.u64 {%0,%1}, [%2];" : "=l"(tabp), "=l"(eap) : "r"(stb + 1024 + lane * 16) : "memory");
    sts128(stb + lane * 16, ident, 0u, 0u, ident);
    sts128(stb + 512 + lane * 16, wx[0], wx[1], wx[2], wx[3]);
    const uint4 id = lds128v(stb + lane * 16);
    { const uint4 w = lds128v(stb + 512 + lane * 16); wx[0] = w.x; wx[1] = w.y; wx[2] = w.z; wx[3] = w.w; }
    float acc[4][4], accp[4];
#pragma unroll
    for (int i = 0; i < 4; i++) { acc[i][0] = acc[i][1] = acc[i][2] = acc[i][3] = 0.f; accp[i] = 0.f; }
    auto switch_window = [&]() {
        __syncwarp();
        sts128(lsb + lane * 16, pack_bf16(acc[0][0], acc[0][1]), pack_bf16(acc[0][2], acc[0][3]), pack_bf16(acc[1][0], acc[1][1]), pack_bf16(acc[1][2], acc[1][3]));
        sts128(lsb + 512 + lane * 16, pack_bf16(acc[2][0], acc[2][1]), pack_bf16(acc[2][2], acc[2][3]), pack_bf16(acc[3][0], acc[3][1]), pack_bf16(acc[3][2], acc[3][3]));
        sts32(lsb + kLQ + lane * 4, pack_bf16(accp[0], accp[1]));
#pragma unroll
        for (int i = 0; i < 4; i++) { acc[i][0] = acc[i][1] = acc[i][2] = acc[i][3] = 0.f; accp[i] = 0.f; }
        ohb += 128;
    };
    uint32_t pS, pQ, pD;
    auto issue = [&](int lo, int st, bool on) {
        const uint4 s4 = lds128(pS + lo);
        const uint32_t q = lds32(pQ + lo);
        cp16g<128>(cpB + st, tabp, s4.x, on);
        cp16g<128>(cpB + st + 512, tabp, s4.y, on);
        cp16g<128>(cpB + st + 1024, tabp, s4.z, on);
        cp16g<128>(cpB + st + 1536, tabp, s4.w, on);
        cp16g<32>(cpB + st + 2048, eap, q & 0xFFFFFFu, on);
        cp_commit();
    };
    auto tile = [&](auto SC, bool on) {
        constexpr int sc = SC.v * kStageBytes, si = ((SC.v + 2) % 3) * kStageBytes, lo = SC.v * 64;
        const uint32_t oa = ohb + (lds32(pD + lo) >> 24);
        issue(lo + 128, si, on);
        uint32_t oh[4], s0, s1;
        ldsm4(oh, oa);
        ldsm2t(s0, s1, oa + 256);
        cp_wait<2>();
        __syncwarp();
        uint32_t ef[4], pa, pb;
        const uint4 x0 = lds128(ldB + sc), x1 = lds128(ldB + sc + 1024);
        ldsm4(ef, ldE + sc);
        float c[2][2][4];
        const uint32_t d0 = hsub2(oh[3], __byte_perm(bitsel<0x003F003Fu>(bitsel<0x00070007u>(x0.x, x0.y << 3), x0.z << 6), 0, 0x2044));
        const uint32_t d1 = hsub2(oh[1], __byte_perm(bitsel<0x003F003Fu>(bitsel<0x00070007u>(x1.x, x1.y << 3), x1.z << 6), 0, 0x2044));
        const uint32_t q0 = hmul2(d0, d0), q1 = hmul2(d1, d1);
        auto pre = [&](int i, uint32_t b00, uint32_t b01, uint32_t b10, uint32_t b11) {
            mma_f16_init(c[i & 1][0], id.x, id.y, id.z, id.w, b00, b01);
            mma_f16_init(c[i & 1][1], id.x, id.y, id.z, id.w, b10, b11);
            mma_bf16(c[i & 1][0], w3[i][0], w3[i][1], w3[i][2], w3[i][3], ef[0], ef[1]);
            mma_bf16(c[i & 1][1], w3[i][0], w3[i][1], w3[i][2], w3[i][3], ef[2], ef[3]);
            mma_bf16(c[i & 1][0], aw[i][0], aw[i][1], aw[i][2], aw[i][3], oh[0], q0);
            mma_bf16(c[i & 1][1], aw[i][0], aw[i][1], aw[i][2], aw[i][3], oh[2], q1);
        };
        auto act = [&](int i) {
            const float* c0 = c[i & 1][0];
            const float* c1 = c[i & 1][1];
            const uint32_t a0 = pack_bf16(silu_half(c0[0]), silu_half(c0[1]));
            const uint32_t a1 = pack_bf16(silu_half(c0[2]), silu_half(c0[3]));
            const uint32_t a2 = pack_bf16(silu_half(c1[0]), silu_half(c1[1]));
            const uint32_t a3 = pack_bf16(silu_half(c1[2]), silu_half(c1[3]));
            pa = i ? hfma2_lo(a0, wx[i], pa) : hmul2_lo(a0, wx[0]);
            pb = i ? hfma2_lo(a2, wx[i], pb) : hmul2_lo(a2, wx[0]);
            pa = hfma2_hi(a1, wx[i], pa);
            pb = hfma2_hi(a3, wx[i], pb);
            mma_bf16(acc[i], a0, a1, a2, a3, s0, s1);
        };
        pre(0, x0.x, x0.y, x1.x, x1.y);
        pre(1, x0.z, x0.w, x1.z, x1.w);
        FENCE(1);
        const uint4 y0 = lds128((ldB ^ 64) + sc), y1 = lds128((ldB ^ 64) + sc + 1024);
        act(0);
        FENCE(2);
        pre(2, y0.x, y0.y, y1.x, y1.y);
        act(1);
        FENCE(3);
        pre(3, y0.z, y0.w, y1.z, y1.w);
        act(2);
        FENCE(4);
        act(3);
        float cs[4];
        mma_bf16_k8_init(cs, movm(pa), movm(pb), 0x3F803F80u);
        const uint32_t cp = pack_bf16(cs[0], cs[2]);
        const uint32_t v0 = hmul2_lo(d0, cp), v1 = hmul2_hi(d1, cp);
        mma_bf16(accp, movm(v0), v0, movm(v1), v1, s0, s1);
    };
    for (;;) {
        int first, nt, sw;
        const uint32_t cnt0 = lds32(sb + SM_WCNT + warp * 4), cnt1 = lds32(sb + SM_WCNT + 64 + warp * 4);
        if (cnt0 <= kCapW && cnt1 <= kCapW) {
            const int n0 = (cnt0 + 15) >> 4, n1 = (cnt1 + 15) >> 4;
            const int i = lane < 16 ? kCapW - 1 - (int)cnt0 - lane : kCapW + (int)cnt1 + lane - 16;
            if (i >= kCapW - 16 * n0 && i < kCapW + 16 * n1) { sts32(lsb + i * 4, nbase); sts32(lsb + kLQ + i * 4, kPadQ | e0); }
            first = kCapW - 16 * n0; nt = n0 + n1; sw = n0;
            if (lane == 0) sts32(sb + SM_CUR + warp * 4, ~0u);
        } else {
            const uint32_t cur = lds32(sb + SM_CUR + warp * 4);
            int n = 0, cur_win = cur >> 24, cur_seg = (cur >> 16) & 255, cur_pos = cur & 0xFFFF;
            while (cur_seg < kG && n <= kCapW - 48) {
                const uint32_t sg = lds32(sb + SM_SEG + cur_seg * 4);
                const int len = 64 + ((sg & 0x1FFF) > 64 ? sg >> 13 : 0), i = cur_pos + lane;
                uint2 v = make_uint2(0, 255);
                if (i < 64) { if (i > 0 && i < (int)(sg & 0x1FFF)) v = __ldcg((const uint2*)g_rec + (cur_seg * kG + cta) * 64 + (i ^ ((2 * cta) & 14))); }
                else if (i < len) {
                    const uint4 o = __ldcg(g_ovf + cur_seg * kChunk + i - 64);
                    if (o.z == cta) v = make_uint2(o.x, o.y);
                }
                const bool hit = (v.y & 255) != 255 && (int)(v.y & 31) == warp + 16 * cur_win;
                const uint32_t bal = __ballot_sync(~0u, hit);
                if (hit) {
                    const int k = kCapW + n + __popc(bal & ((1u << lane) - 1));
                    sts32(lsb + k * 4, v.x & 0x7FFFu);
                    sts32(lsb + kLQ + k * 4, ((v.x >> 15) + cur_seg * kChunk) | ((v.y << 23) & 0x70000000u));
                }
                n += __popc(bal);
                cur_pos += 32;
                if (cur_pos >= len) { cur_pos = 0; cur_seg++; }
            }
            if (lane < 16) { sts32(lsb + (kCapW + n + lane) * 4, nbase); sts32(lsb + kLQ + (kCapW + n + lane) * 4, kPadQ | e0); }
            first = kCapW; nt = (n + 15) >> 4; sw = nt + 1;
            uint32_t nxt = (cur_win << 24) | (cur_seg << 16) | cur_pos;
            if (cur_seg == kG) {
                if (cur_win == 0) { sw = nt; nxt = 1u << 24; } else nxt = ~0u;
            }
            __syncwarp();
            if (lane == 0) sts32(sb + SM_CUR + warp * 4, nxt);
        }
        __syncwarp();
        pS = lsb + first * 4 + (lane >> 3) * 16;
        const int pe = (lane ^ ((lane >> 1) & 4)) >> 1, pd = (lane ^ ((lane >> 1) & 8)) & 15;
        pQ = lsb + kLQ + (first + 4 * (pe & 3) + (pe >> 2)) * 4;
        pD = lsb + kLQ + (first + 4 * (pd & 3) + (pd >> 2)) * 4;
        issue(0, 0, nt > 0);
        issue(64, kStageBytes, nt > 1);
        const uint32_t pEnd = pS + nt * 64;
        uint32_t pSw = pS + sw * 64;
#pragma unroll 1
        for (;;) {
            if (pS == pSw) switch_window();
            if (pS == pEnd) break;
            tile(IC<0>(), pS + 128 < pEnd);
            if (pS + 64 == pSw) switch_window();
            if (pS + 64 == pEnd) break;
            tile(IC<1>(), pS + 192 < pEnd);
            if (pS + 128 == pSw) switch_window();
            if (pS + 128 == pEnd) break;
            tile(IC<2>(), pS + 256 < pEnd);
            pS += 192; pQ += 192; pD += 192;
        }
        __syncwarp();
        if (lds32(sb + SM_CUR + warp * 4) == ~0u) break;
    }
    TSTAMP(7);

    {
#pragma unroll
        for (int j = 0; j < 4; j++) {
            const int r = j * 4 + (lane >> 3), c = lane & 7, dloc = warp + 16 * (r >> 3) + 32 * (r & 7);
            const bool ok = dloc < ncta;
            cp16z(stb + r * 128 + ((c ^ (r & 7)) << 4), (const uint4*)h + (size_t)(ok ? nbase + dloc : 0) * 8 + c, ok ? 0u : ~0u);
        }
        cp_commit();
        const uint4 ma = lds128(lsb + lane * 16), mb = lds128(lsb + 512 + lane * 16);
        const uint32_t m0[4][2] = {{ma.x, ma.y}, {ma.z, ma.w}, {mb.x, mb.y}, {mb.z, mb.w}};
        float c[8][4];
#pragma unroll
        for (int j = 0; j < 8; j++) { c[j][0] = c[j][1] = c[j][2] = c[j][3] = 0.f; }
        uint32_t hf[4][4];
#pragma unroll
        for (int kk = 0; kk < 8; kk++) {
            const int ks = kk ^ 4;
            uint32_t a[4];
            if (ks < 4) {
                if (ks == 0) { cp_wait<0>(); __syncwarp(); }
                const int r = lane & 15;
                ldsm4(hf[ks], stb + r * 128 + (((2 * ks + (lane >> 4)) ^ (r & 7)) << 4));
                a[0] = hf[ks][0]; a[1] = hf[ks][1]; a[2] = hf[ks][2]; a[3] = hf[ks][3];
            } else {
                const int i = ks - 4;
                a[0] = movm(m0[i][0]);
                a[1] = movm(pack_bf16(acc[i][0], acc[i][1]));
                a[2] = movm(m0[i][1]);
                a[3] = movm(pack_bf16(acc[i][2], acc[i][3]));
            }
#pragma unroll
            for (int i = 0; i < 4; i++) {
                uint32_t w[4];
                const int k = 16 * ks + (lane & 7) + ((lane >> 4) << 3);
                ldsm4t(w, sb + SM_WH + k * 128 + (((2 * i + ((lane >> 3) & 1)) ^ (k & 7)) << 4));
                mma_bf16(c[2 * i], a[0], a[1], a[2], a[3], w[0], w[2]);
                mma_bf16(c[2 * i + 1], a[0], a[1], a[2], a[3], w[1], w[3]);
            }
            if (kk == 3 && (g & 1) && g < 6 && t < 3) {
                const uint32_t dl[2] = {lds32(lsb + kLQ + lane * 4), pack_bf16(accp[0], accp[1])};
#pragma unroll
                for (int sub = 0; sub < 2; sub++) {
                    const uint32_t pa = sb + SM_POS + warp * 512 + sub * 128 + t * 32 + (g >> 1) * 4;
                    const uint32_t o = hadd2(__byte_perm(lds32(pa), lds32(pa + 16), 0x7632), dl[sub]);
                    const int dloc = warp + 16 * sub + 64 * t;
                    unsigned short* op = (unsigned short*)out_pos + (size_t)(nbase + dloc) * 3 + (g >> 1);
                    if (dloc < ncta) op[0] = (unsigned short)o;
                    if (dloc + 32 < ncta) op[96] = (unsigned short)(o >> 16);
                }
            }
        }
        __syncwarp();
#pragma unroll
        for (int ks = 0; ks < 4; ks++) {
            uint32_t o[4];
#pragma unroll
            for (int q = 0; q < 4; q++) {
                const float* cc = c[2 * ks + (q >> 1)] + 2 * (q & 1);
                o[q] = hadd2(hf[ks][q], pack_bf16(silu_half(0.5f * cc[0]), silu_half(0.5f * cc[1])));
            }
            const int r = lane & 15;
            stsm4(stb + r * 128 + (((2 * ks + (lane >> 4)) ^ (r & 7)) << 4), o[0], o[1], o[2], o[3]);
        }
        __syncwarp();
#pragma unroll
        for (int j = 0; j < 4; j++) {
            const int r = j * 4 + (lane >> 3), cc = lane & 7, dloc = warp + 16 * (r >> 3) + 32 * (r & 7);
            const uint4 v = lds128(stb + r * 128 + ((cc ^ (r & 7)) << 4));
            if (dloc < ncta) ((uint4*)out_h)[(size_t)(nbase + dloc) * 8 + cc] = v;
        }
    }
    if (tid == 0) g_epoch[cta] = epoch;
    TSTAMP(8);
}

}

extern "C" void kernel_launch(void* const* d_in, const int* in_sizes, int n_in, void* d_out, int out_size) {
    static bool init = false;
    if (!init) {
        cudaFuncSetAttribute(egnn_kernel, cudaFuncAttributeMaxDynamicSharedMemorySize, SM_TOTAL);
        init = true;
    }
    __nv_bfloat16* out = (__nv_bfloat16*)d_out;
    egnn_kernel<<<kG, kThreads, SM_TOTAL>>>(
        (const __nv_bfloat16*)d_in[0], (const __nv_bfloat16*)d_in[1], (const __nv_bfloat16*)d_in[2],
        (const int*)d_in[3], (const int*)d_in[4], (const __nv_bfloat16*)d_in[5],
        (const __nv_bfloat16*)d_in[6], (const __nv_bfloat16*)d_in[7], out, out + (size_t)kN * 64);
}
```

```cpp
#include <cuda_runtime.h>
#include <cuda_bf16.h>
#include <cuda_fp16.h>
#include <stdint.h>

namespace {

constexpr int kN = 25000;
constexpr int kE = 800000;
constexpr int kG = 132;
constexpr int kNPC = 190;
constexpr int kChunk = 6064;
constexpr int kThreads = 512;
constexpr int kWarps = 16;
constexpr int kCapW = 272;
constexpr int kStageBytes = 2560;
constexpr int kStageStride = kWarps * kStageBytes;
constexpr int kSegPerWarp = 9;
constexpr int kCol = kWarps - 1;
constexpr int kPosStride = 528;
constexpr uint32_t kBinMul = 22605092u;
constexpr unsigned kSpinLimit = 1u << 22;
constexpr uint32_t kPadQ = 6u << 28;

constexpr int SM_STAGE = 0;
constexpr int SM_REC = SM_STAGE;
constexpr int SM_WE = SM_STAGE + kG * 512;
constexpr int SM_H = SM_WE + 145 * 128;
constexpr int SM_A = SM_H + 192 * 128;
constexpr int SM_W3 = SM_A - 17 * 128;
constexpr int SM_H2 = SM_STAGE + 3 * kStageStride;
constexpr int SM_LS = SM_A + 192 * 128;
constexpr int kLQ = kWarps * 2 * kCapW * 4;
constexpr int SM_WH = SM_LS + 2 * kLQ;
constexpr int SM_POS = SM_WH + 16384;
constexpr int SM_OH = SM_POS + kWarps * kPosStride;
constexpr int SM_WX = SM_OH + 512;
constexpr int SM_HIST = SM_WX + 128;
constexpr int SM_WCNT = SM_HIST + 144 * 4;
constexpr int SM_MISC = SM_WCNT + 32 * 4;
constexpr int SM_CUR = SM_MISC + 32;
constexpr int SM_SEG = SM_CUR + 64;
constexpr int SM_TOTAL = SM_SEG + 144 * 4;
static_assert(SM_W3 >= 2 * kStageStride && SM_LS >= SM_H2 + kWarps * 768, "aliasing");
static_assert(SM_TOTAL <= 232448, "shared memory");

__device__ uint4 g_tab[kG * kNPC * 8];
__device__ uint4 g_rec[kG * kG * 32];
__device__ uint4 g_ovf[kG * kChunk];
__device__ uint4 g_flag0[17];
__device__ __align__(128) unsigned g_hdr[kG * 160];
__device__ unsigned g_epoch[kG];
#define TDEP(i, x)
#define TSTAMP(i)

__device__ __forceinline__ void mma_bf16(float (&c)[4], uint32_t a0, uint32_t a1, uint32_t a2, uint32_t a3, uint32_t b0, uint32_t b1) {
    asm volatile("mma.sync.aligned.m16n8k16.row.col.f32.bf16.bf16.f32 {%0,%1,%2,%3}, {%4,%5,%6,%7}, {%8,%9}, {%0,%1,%2,%3};"
        : "+f"(c[0]), "+f"(c[1]), "+f"(c[2]), "+f"(c[3]) : "r"(a0), "r"(a1), "r"(a2), "r"(a3), "r"(b0), "r"(b1));
}
__device__ __forceinline__ void mma_f16(float (&c)[4], const uint32_t (&a)[4], uint32_t b0, uint32_t b1) {
    asm volatile("mma.sync.aligned.m16n8k16.row.col.f32.f16.f16.f32 {%0,%1,%2,%3}, {%4,%5,%6,%7}, {%8,%9}, {%0,%1,%2,%3};"
        : "+f"(c[0]), "+f"(c[1]), "+f"(c[2]), "+f"(c[3]) : "r"(a[0]), "r"(a[1]), "r"(a[2]), "r"(a[3]), "r"(b0), "r"(b1));
}
__device__ __forceinline__ void mma_h(uint32_t& c0, uint32_t& c1, const uint32_t (&a)[4], uint32_t b0, uint32_t b1) {
    asm volatile("mma.sync.aligned.m16n8k16.row.col.f16.f16.f16.f16 {%0,%1}, {%2,%3,%4,%5}, {%6,%7}, {%0,%1};"
        : "+r"(c0), "+r"(c1) : "r"(a[0]), "r"(a[1]), "r"(a[2]), "r"(a[3]), "r"(b0), "r"(b1));
}
__device__ __forceinline__ void mma_f16_k8_init(float (&c)[4], uint32_t a0, uint32_t a1, uint32_t b0) {
    asm volatile("mma.sync.aligned.m16n8k8.row.col.f32.f16.f16.f32 {%0,%1,%2,%3}, {%4,%5}, {%6}, {%7,%7,%7,%7};"
        : "=f"(c[0]), "=f"(c[1]), "=f"(c[2]), "=f"(c[3]) : "r"(a0), "r"(a1), "r"(b0), "f"(0.f));
}
__device__ __forceinline__ uint32_t movm(uint32_t a) {
    uint32_t d; asm("movmatrix.sync.aligned.m8n8.trans.b16 %0, %1;" : "=r"(d) : "r"(a)); return d;
}
__device__ __forceinline__ void ldsm4(uint32_t (&r)[4], uint32_t a) {
    asm volatile("ldmatrix.sync.aligned.m8n8.x4.shared.b16 {%0,%1,%2,%3}, [%4];" : "=r"(r[0]), "=r"(r[1]), "=r"(r[2]), "=r"(r[3]) : "r"(a));
}
__device__ __forceinline__ void ldsm4t(uint32_t (&r)[4], uint32_t a) {
    asm volatile("ldmatrix.sync.aligned.m8n8.x4.trans.shared.b16 {%0,%1,%2,%3}, [%4];" : "=r"(r[0]), "=r"(r[1]), "=r"(r[2]), "=r"(r[3]) : "r"(a));
}
__device__ __forceinline__ void stsm4(uint32_t a, uint32_t r0, uint32_t r1, uint32_t r2, uint32_t r3) {
    asm volatile("stmatrix.sync.aligned.m8n8.x4.shared.b16 [%0], {%1,%2,%3,%4};" :: "r"(a), "r"(r0), "r"(r1), "r"(r2), "r"(r3) : "memory");
}
__device__ __forceinline__ uint4 lds128(uint32_t a) {
    uint4 v; asm volatile("ld.shared.v4.u32 {%0,%1,%2,%3}, [%4];" : "=r"(v.x), "=r"(v.y), "=r"(v.z), "=r"(v.w) : "r"(a)); return v;
}
__device__ __forceinline__ uint4 lds128v(uint32_t a) {
    uint4 v; asm volatile("ld.volatile.shared.v4.u32 {%0,%1,%2,%3}, [%4];" : "=r"(v.x), "=r"(v.y), "=r"(v.z), "=r"(v.w) : "r"(a) : "memory"); return v;
}
__device__ __forceinline__ uint32_t lds32(uint32_t a) {
    uint32_t v; asm volatile("ld.shared.u32 %0, [%1];" : "=r"(v) : "r"(a)); return v;
}
__device__ __forceinline__ uint32_t lds16(uint32_t a) {
    uint32_t v; asm volatile("ld.shared.u16 %0, [%1];" : "=r"(v) : "r"(a)); return v;
}
__device__ __forceinline__ void sts32(uint32_t a, uint32_t v) { asm volatile("st.shared.u32 [%0], %1;" :: "r"(a), "r"(v) : "memory"); }
__device__ __forceinline__ void sts64(uint32_t a, uint32_t x, uint32_t y) { asm volatile("st.shared.v2.u32 [%0], {%1,%2};" :: "r"(a), "r"(x), "r"(y) : "memory"); }
__device__ __forceinline__ uint32_t atoms_inc(uint32_t a) {
    uint32_t v; asm volatile("atom.shared.add.u32 %0, [%1], 1;" : "=r"(v) : "r"(a) : "memory"); return v;
}
__device__ __forceinline__ uint32_t atoms_inc_lt(uint32_t a, uint32_t i, uint32_t n) {
    uint32_t v; asm volatile("{.reg .pred p; setp.lt.u32 p, %2, %3; mov.b32 %0, -1; @p atom.shared.add.u32 %0, [%1], 1;}" : "=r"(v) : "r"(a), "r"(i), "r"(n) : "memory"); return v;
}
__device__ __forceinline__ void cp16(uint32_t d, const void* s) {
    asm volatile("cp.async.cg.shared.global [%0], [%1], 16;" :: "r"(d), "l"(s) : "memory");
}
__device__ __forceinline__ void cp16z(uint32_t d, const void* s, uint32_t flag) {
    asm volatile("{.reg .pred p; setp.lt.s32 p, %2, 0; cp.async.cg.shared.global [%0], [%1], 16, p;}" :: "r"(d), "l"(s), "r"(flag) : "memory");
}
__device__ __forceinline__ void cp_commit() { asm volatile("cp.async.commit_group;" ::: "memory"); }
template <int n> __device__ __forceinline__ void cp_wait() { asm volatile("cp.async.wait_group %0;" :: "n"(n) : "memory"); }
__device__ __forceinline__ int4 ldg_stream(const int4* p) {
    int4 v; asm volatile("ld.relaxed.gpu.global.v4.s32 {%0,%1,%2,%3}, [%4];" : "=r"(v.x), "=r"(v.y), "=r"(v.z), "=r"(v.w) : "l"(p) : "memory"); return v;
}
__device__ __forceinline__ uint32_t ldg16(const unsigned short* p) {
    uint32_t v; asm volatile("ld.relaxed.gpu.global.u16 %0, [%1];" : "=r"(v) : "l"(p) : "memory"); return v;
}
__device__ __forceinline__ uint32_t pack_bf16(float lo, float hi) {
    uint32_t d; asm("cvt.rn.bf16x2.f32 %0, %1, %2;" : "=r"(d) : "f"(hi), "f"(lo)); return d;
}
__device__ __forceinline__ uint32_t pack_f16(float lo, float hi) {
    uint32_t d; asm("cvt.rn.f16x2.f32 %0, %1, %2;" : "=r"(d) : "f"(hi), "f"(lo)); return d;
}
__device__ __forceinline__ uint32_t hmul2(uint32_t a, uint32_t b) { uint32_t d; asm("mul.rn.bf16x2 %0, %1, %2;" : "=r"(d) : "r"(a), "r"(b)); return d; }
__device__ __forceinline__ uint32_t hsub2(uint32_t a, uint32_t b) { uint32_t d; asm("sub.rn.bf16x2 %0, %1, %2;" : "=r"(d) : "r"(a), "r"(b)); return d; }
__device__ __forceinline__ uint32_t hadd2(uint32_t a, uint32_t b) { uint32_t d; asm("add.rn.bf16x2 %0, %1, %2;" : "=r"(d) : "r"(a), "r"(b)); return d; }
__device__ __forceinline__ float silu_half(float x) {
    float t; asm volatile("tanh.approx.f32 %0, %1;" : "=f"(t) : "f"(x)); return fmaf(x, t, x);
}
__device__ __forceinline__ uint32_t silu_half2(uint32_t x) {
    uint32_t d; asm volatile("{.reg .b32 t; tanh.approx.f16x2 t, %1; fma.rn.f16x2 %0, %1, t, %1;}" : "=r"(d) : "r"(x)); return d;
}
__device__ __forceinline__ uint32_t bf2h(uint32_t x) { return pack_f16(__uint_as_float(x << 16), __uint_as_float(x & 0xFFFF0000u)); }
__device__ __forceinline__ int feat(int p) { return (p & 33) | ((p & 6) << 2) | ((p >> 2) & 6); }
__device__ __forceinline__ void ldsm2t(uint32_t& r0, uint32_t& r1, uint32_t a) {
    asm volatile("ldmatrix.sync.aligned.m8n8.x2.trans.shared.b16 {%0,%1}, [%2];" : "=r"(r0), "=r"(r1) : "r"(a));
}
__device__ __forceinline__ void sts128(uint32_t a, uint32_t x, uint32_t y, uint32_t z, uint32_t w) {
    asm volatile("st.shared.v4.u32 [%0], {%1,%2,%3,%4};" :: "r"(a), "r"(x), "r"(y), "r"(z), "r"(w) : "memory");
}
template <int mul> __device__ __forceinline__ void cp16g(uint32_t d, uint64_t base, uint32_t idx, bool p) {
    asm volatile("{.reg .pred p; .reg .b64 a; setp.ne.u32 p, %3, 0; mul.wide.u32 a, %2, %4; add.s64 a, a, %1; @p cp.async.cg.shared.global [%0], [a], 16;}"
                 :: "r"(d), "l"(base), "r"(idx), "r"((uint32_t)p), "n"(mul) : "memory");
}
template <uint32_t m> __device__ __forceinline__ uint32_t bitsel(uint32_t a, uint32_t b) {
    uint32_t d; asm("lop3.b32 %0, %1, %2, %3, 0xE2;" : "=r"(d) : "r"(a), "n"(m), "r"(b)); return d;
}
__device__ __forceinline__ uint32_t hfma2_lo(uint32_t a, uint32_t b, uint32_t c) {
    uint32_t d; asm("{.reg .b16 l,h; .reg .b32 x; mov.b32 {l,h}, %2; mov.b32 x, {l,l}; fma.rn.f16x2 %0, %1, x, %3;}" : "=r"(d) : "r"(a), "r"(b), "r"(c)); return d;
}
__device__ __forceinline__ uint32_t hfma2_hi(uint32_t a, uint32_t b, uint32_t c) {
    uint32_t d; asm("{.reg .b16 l,h; .reg .b32 x; mov.b32 {l,h}, %2; mov.b32 x, {h,h}; fma.rn.f16x2 %0, %1, x, %3;}" : "=r"(d) : "r"(a), "r"(b), "r"(c)); return d;
}
__device__ __forceinline__ uint4 ld_relaxed(const uint4* p) {
    uint4 v; asm volatile("ld.relaxed.gpu.global.v4.u32 {%0,%1,%2,%3}, [%4];" : "=r"(v.x), "=r"(v.y), "=r"(v.z), "=r"(v.w) : "l"(p) : "memory"); return v;
}
__device__ __forceinline__ void st_relaxed(uint4* p, uint32_t x, uint32_t y, uint32_t z, uint32_t w) {
    asm volatile("st.relaxed.gpu.global.v4.u32 [%0], {%1,%2,%3,%4};" :: "l"(p), "r"(x), "r"(y), "r"(z), "r"(w) : "memory");
}
__device__ __forceinline__ uint32_t hmul2_lo(uint32_t a, uint32_t b) {
    uint32_t d; asm("{.reg .b16 l,h; .reg .b32 x; mov.b32 {l,h}, %2; mov.b32 x, {l,l}; mul.rn.bf16x2 %0, %1, x;}" : "=r"(d) : "r"(a), "r"(b)); return d;
}
__device__ __forceinline__ uint32_t hmul2_hi(uint32_t a, uint32_t b) {
    uint32_t d; asm("{.reg .b16 l,h; .reg .b32 x; mov.b32 {l,h}, %2; mov.b32 x, {h,h}; mul.rn.bf16x2 %0, %1, x;}" : "=r"(d) : "r"(a), "r"(b)); return d;
}
template <int n> __device__ __forceinline__ uint32_t embed_bits(uint32_t w, uint32_t r) {
    constexpr uint32_t m = ((1u << n) - 1) * 0x10001u;
    r &= m;
    const uint32_t v = __vmaxu2((w & 0x7FFF7FFFu) + (0x10001u << (n - 1)), r) - r;
    return (v & ~m) | r | (w & 0x80008000u);
}

template <class F>
__device__ __forceinline__ uint32_t project(uint32_t sb, int warp, int lane, F hook, uint4 (&tw)[6]) {
    const int g = lane >> 2, t = lane & 3, row0 = (warp & 3) * 48, cg = warp >> 2;
    float c[3][4][4];
#pragma unroll
    for (int m = 0; m < 3; m++)
#pragma unroll
        for (int j = 0; j < 4; j++) { c[m][j][0] = c[m][j][1] = c[m][j][2] = c[m][j][3] = 0.f; }
    const uint32_t wa = sb + SM_WE + ((cg < 2 ? 64 : 0) + (lane & 7) + ((lane >> 4) << 3)) * 128 + (((4 * (cg & 1) + ((lane >> 3) & 1)) ^ (lane & 7)) << 4);
    const uint32_t ha = sb + SM_H + (row0 + (lane & 15)) * 128 + (((lane >> 4) ^ (lane & 7)) << 4);
#pragma unroll
    for (int ks = 0; ks < 4; ks++) {
        uint32_t w[2][4];
        ldsm4t(w[0], wa + ks * 2048);
        ldsm4t(w[1], (wa ^ 32) + ks * 2048);
#pragma unroll
        for (int m = 0; m < 3; m++) {
            uint32_t hf[4];
            ldsm4(hf, (ha ^ (ks << 5)) + m * 2048);
            hook(ks * 3 + m);
#pragma unroll
            for (int j = 0; j < 4; j++) mma_bf16(c[m][j], hf[0], hf[1], hf[2], hf[3], w[j >> 1][j & 1], w[j >> 1][2 + (j & 1)]);
        }
    }
    float mx = 0.f;
#pragma unroll
    for (int m = 0; m < 3; m++)
#pragma unroll
        for (int u = 0; u < 2; u++) {
            uint32_t wd[4];
#pragma unroll
            for (int j = 0; j < 4; j++) {
                mx = fmaxf(mx, fmaxf(fabsf(c[m][j][2 * u]), fabsf(c[m][j][2 * u + 1])));
                wd[j] = pack_f16(c[m][j][2 * u] * 0.5f, c[m][j][2 * u + 1] * 0.5f);
            }
            const int r = row0 + 16 * m;
            if (cg == 0) {
                const uint32_t p = __byte_perm(lds32(sb + SM_POS + (8 * u + g) * kPosStride + (r & 16) * 8 + (r >> 5) * 16 + 4 * t), 0, 0x4342);
                wd[0] = embed_bits<3>(wd[0], p);
                wd[1] = embed_bits<3>(wd[1], p >> 3);
                wd[2] = embed_bits<2>(wd[2], p >> 6);
            }
            tw[2 * m + u] = make_uint4(wd[0], wd[1], wd[2], wd[3]);
            if (cg >= 2) sts128(sb + SM_A + (r + 8 * u + g) * 128 + (((4 * (cg & 1) + t) ^ ((g + (r >> 5)) & 7)) << 4), wd[0], wd[1], wd[2], wd[3]);
        }
    return __float_as_uint(mx * 0.5f);
}

__device__ __forceinline__ void put_table(const uint4 (&tw)[6], int warp, int lane, int nbase, int ncta) {
    const int r = (warp & 3) * 48 + (lane >> 2);
#pragma unroll
    for (int i = 0; i < 6; i++)
        if (r + 8 * i < ncta) st_relaxed(g_tab + (size_t)(nbase + r + 8 * i) * 8 + (warp >> 2) * 4 + (lane & 3), tw[i].x, tw[i].y, tw[i].z, tw[i].w);
}
#define SE 9
#define PS 400
__device__ __forceinline__ int fresh_lane() { int l; asm volatile("mov.u32 %0, %%laneid;" : "=r"(l)); return l; }

__device__ __noinline__ void exact_window(const __nv_bfloat16* h, const __nv_bfloat16* pos, const __nv_bfloat16* e_attr,
                                          const __nv_bfloat16* w_e, const __nv_bfloat16* w_x, const uint32_t* seg, float* buf, int win) {
    const int lane = threadIdx.x & 31, cta = blockIdx.x;
    auto rb = [](float x) { return __bfloat162float(__float2bfloat16(x)); };
    for (int i = lane; i < 6 * 68; i += 32) buf[i] = 0.f;
    __syncwarp();
    for (int b = 0; b < kG; b++) {
        const int cnt = seg[b] & 0x1FFF, len = cnt > 64 ? 64 + (seg[b] >> 13) : cnt;
        for (int i0 = 0; i0 < len; i0 += 32) {
            const int i = i0 + lane;
            uint2 v = make_uint2(0, 255);
            if (i < 64) { if (i < cnt) v = __ldcg((const uint2*)g_rec + (b * kG + cta) * 64 + (i ^ ((2 * cta) & 14))); }
            else if (i < len) {
                const uint4 o = __ldcg(g_ovf + b * kChunk + i - 64);
                if (o.z == cta) v = make_uint2(o.x, o.y);
            }
            for (uint32_t bal = __ballot_sync(~0u, (v.y & 255) != 255 && (int)(v.y & 31) == win); bal; bal &= bal - 1) {
                const uint32_t w0 = __shfl_sync(~0u, v.x, __ffs(bal) - 1), dl = __shfl_sync(~0u, v.y, __ffs(bal) - 1) & 255;
                const int sn = w0 & 0x7FFF, dn = cta * kNPC + dl, e = (w0 >> 15) + b * kChunk;
                float df[3], d2 = 0.f, p0 = 0.f, p1 = 0.f;
                for (int c = 0; c < 3; c++) {
                    df[c] = rb(__bfloat162float(pos[dn * 3 + c]) - __bfloat162float(pos[sn * 3 + c]));
                    d2 += rb(df[c] * df[c]);
                }
                for (int k = 0; k < 145; k++) {
                    const float x = k == 128 ? rb(d2) : __bfloat162float(k < 64 ? h[dn * 64 + k] : k < 128 ? h[sn * 64 + k - 64] : e_attr[(size_t)e * 16 + k - 129]);
                    p0 = fmaf(x, __bfloat162float(w_e[k * 64 + lane]), p0);
                    p1 = fmaf(x, __bfloat162float(w_e[k * 64 + 32 + lane]), p1);
                }
                p0 = rb(silu_half(0.5f * rb(p0)));
                p1 = rb(silu_half(0.5f * rb(p1)));
                float cs = p0 * __bfloat162float(w_x[lane]) + p1 * __bfloat162float(w_x[32 + lane]);
                for (int o = 16; o; o >>= 1) cs += __shfl_xor_sync(~0u, cs, o);
                buf[(dl >> 5) * 64 + lane] += p0;
                buf[(dl >> 5) * 64 + 32 + lane] += p1;
                if (lane < 3) buf[384 + (dl >> 5) * 4 + lane] += rb((lane == 0 ? df[0] : lane == 1 ? df[1] : df[2]) * rb(cs));
            }
        }
    }
    __syncwarp();
}

__global__ void __launch_bounds__(kThreads, 1)
egnn_kernel(const __nv_bfloat16* __restrict__ h, const __nv_bfloat16* __restrict__ pos,
            const __nv_bfloat16* __restrict__ e_attr, const int* __restrict__ src,
            const int* __restrict__ dst, const __nv_bfloat16* __restrict__ w_e,
            const __nv_bfloat16* __restrict__ w_x, const __nv_bfloat16* __restrict__ w_h,
            __nv_bfloat16* __restrict__ out_h, __nv_bfloat16* __restrict__ out_pos) {
    extern __shared__ __align__(128) unsigned char smem[];
    const uint32_t sb = (uint32_t)__cvta_generic_to_shared(smem);
    const int tid = threadIdx.x, lane = tid & 31;
    const int warp = __reduce_max_sync(~0u, tid >> 5);
    const int g = lane >> 2, t = lane & 3;
    const int cta = blockIdx.x;
    TSTAMP(0);

    const int e0 = cta * kChunk;
    const int ne4 = min(kChunk, kE - e0) >> 2;
    int4 dv[3], sv[3];
#pragma unroll
    for (int k = 0; k < 3; k++) dv[k] = ldg_stream((const int4*)(dst + e0) + min(tid + k * kThreads, ne4 - 1));
    unsigned epoch;
    asm volatile("ld.relaxed.gpu.global.u32 %0, [%1];" : "=r"(epoch) : "l"(g_epoch + cta) : "memory");
#pragma unroll
    for (int k = 0; k < 3; k++) sv[k] = ldg_stream((const int4*)(src + e0) + min(tid + k * kThreads, ne4 - 1));
    const int nbase = cta * kNPC;
    const int ncta = min(kNPC, kN - nbase);
    uint32_t px = 0, py = 0, pz = 0;
    {
        const int dloc = warp + 16 * (lane >> 3) + 32 * (lane & 7);
        if (lane < 16 && (lane & 7) < 6 && dloc < ncta) {
            const unsigned short* p = (const unsigned short*)pos + (size_t)(nbase + dloc) * 3;
            px = ldg16(p); py = ldg16(p + 1); pz = ldg16(p + 2);
        }
    }
#pragma unroll
    for (int k = 0; k < 9; k++) {
        const int i = tid + k * kThreads;
        if (i < kG * 32) sts128(sb + SM_REC + i * 16, 0u, 0u, 0u, 0u);
    }
    if (tid < 144 + 32 + 8 + 16) sts32(sb + SM_HIST + tid * 4, 0u);
    else if (tid >= 256 && tid < 384) {
        const int w = tid - 256, r = (w >> 2) & 7, j = w < 64 ? r + 6 * (w >> 5) : r;
        sts32(sb + SM_OH + w * 4, (r < 6 && (j >> 1) == (w & 3)) ? 0x3C00u << ((j & 1) * 16) : 0u);
    }
    __syncthreads();
#pragma unroll
    for (int q = 0; q < 3; q++) {
        const int i = tid + q * kThreads, r = i >> 3, c = i & 7;
        if (i < 145 * 8) cp16(sb + SM_WE + r * 128 + ((c ^ (r & 7)) << 4), (const uint4*)w_e + i);
    }
    if (tid >= kThreads - 8) cp16(sb + SM_WX + (tid & 7) * 16, (const uint4*)w_x + (tid & 7));
#pragma unroll
    for (int q = 0; q < 3; q++) {
        const int i = tid + q * kThreads, r = i >> 3, c = i & 7;
        const bool ok = r < ncta;
        cp16z(sb + SM_H + r * 128 + ((c ^ (r & 7)) << 4), (const uint4*)h + (ok ? (size_t)nbase * 8 + i : 0), ok ? 0u : ~0u);
    }
    cp_commit();
    epoch += (epoch & 0xFFFFFFu) == 0xFFFFFFu ? 2 : 1;
    const uint32_t tag = epoch << 8;
    TDEP(11, dv[0].x);

#pragma unroll
    for (int k = 0; k < 3; k++) {
        const int i = tid + k * kThreads;
        const int d4[4] = {dv[k].x, dv[k].y, dv[k].z, dv[k].w};
        const int s4[4] = {sv[k].x, sv[k].y, sv[k].z, sv[k].w};
        if (k < 2 || i < ne4) {
            uint32_t bin[4], rank[4];
#pragma unroll
            for (int q = 0; q < 4; q++) {
                bin[q] = __umulhi((uint32_t)d4[q], kBinMul);
                rank[q] = atoms_inc(sb + SM_HIST + bin[q] * 4);
            }
#pragma unroll
            for (int q = 0; q < 4; q++) {
                const uint32_t w0 = (uint32_t)s4[q] + ((uint32_t)(i * 4 + q) << 15);
                const uint32_t w1 = (uint32_t)d4[q] + tag - bin[q] * kNPC;
                if (rank[q] < 64) sts64(sb + SM_REC + bin[q] * 512 + ((rank[q] ^ ((2 * bin[q]) & 14)) << 3), w0, w1);
            }
            if ((rank[0] | rank[1] | rank[2] | rank[3]) >= 64) {
#pragma unroll
                for (int q = 0; q < 4; q++) {
                    if (rank[q] >= 64) {
                        const uint32_t w1 = (uint32_t)d4[q] + tag - bin[q] * kNPC;
                        st_relaxed(g_ovf + cta * kChunk + atoms_inc(sb + SM_MISC + 8), (uint32_t)s4[q] + ((uint32_t)(i * 4 + q) << 15), w1, bin[q], w1);
                    }
                }
            }
        }
    }
    if (lane < 16) {
        const int j = 6 * (lane >> 3) + (lane & 7);
        const bool v = (lane & 7) < 6;
        sts128(sb + SM_POS + warp * kPosStride + lane * 16, (px << 16) | (v && j == 8 ? 0x3F80u : 0u), (py << 16) | (v && j == 9 ? 0x3F80u : 0u),
               (pz << 16) | (v && j == 10 ? 0x3F80u : 0u), v && j == 11 ? 0x3F80u : 0u);
    } else {
        const uint32_t o = 0x3C00u << ((lane & 1) * 16), r = (lane & 7) >> 1;
        sts128(sb + SM_POS + warp * kPosStride + lane * 16, r == 0 ? o : 0u, r == 1 ? o : 0u, r == 2 ? o : 0u, 0u);
    }
    TSTAMP(1);
    if (SE == 0) cp_wait<0>();
    __syncthreads();
    TDEP(14, lds32(sb + SM_HIST));
    uint4 tw[6];
    {
        const uint32_t novf = lds32(sb + SM_MISC + 8);
        if (tid < 136) asm volatile("st.relaxed.gpu.global.u32 [%0], %1;" :: "l"(g_hdr + cta * 160 + tid), "r"(lds32(sb + SM_HIST + tid * 4) | (novf << 13) | (epoch << 26)) : "memory");
        if (tid == 160 && (novf & 1)) st_relaxed(g_ovf + cta * kChunk + novf, 0u, 0u, 0u, 0u);
        const uint32_t lim = ((lane ^ (warp & 7)) >> 1) * 4;
        auto send = [&](int s) {
            if (s < 9 && lim < lds32(sb + SM_HIST + (s * kWarps + warp) * 4)) {
                const uint4 v = lds128(sb + SM_REC + s * (kWarps * 512) + tid * 16);
                st_relaxed(g_rec + cta * (kG * 32) + s * kThreads + tid, v.x, v.y, v.z, v.w);
            }
        };
#pragma unroll
        for (int s = 0; s < SE; s++) send(s);
        if (SE) {
            cp_wait<0>();
            TSTAMP(12);
            __syncthreads();
        }
        uint32_t mx = project(sb, warp, lane, [&](int step) { send(SE + step); }, tw);
        if (warp < 8) {
            mx = __reduce_max_sync(~0u, mx);
            if (lane == 0) asm volatile("red.shared.max.u32 [%0], %1;" :: "r"(sb + SM_MISC), "r"(mx) : "memory");
        }
    }
    TSTAMP(13);
    const unsigned* hdrp = g_hdr + min(lane * kCol + warp, kG - 1) * 160 + cta;
    uint32_t hdr;
    asm volatile("ld.relaxed.gpu.global.u32 %0, [%1];" : "=r"(hdr) : "l"(hdrp) : "memory");
#pragma unroll
    for (int q = 0; q < 2; q++) {
        const int i = tid + q * kThreads, r = i >> 3, c = i & 7;
        cp16(sb + SM_WH + r * 128 + ((c ^ (r & 7)) << 4), (const uint4*)w_h + (q ? 64 + feat(r - 64) : r) * 8 + c);
    }
    cp_commit();
    __syncthreads();
    TSTAMP(3);

    auto place = [&](uint32_t w0, uint32_t x, uint32_t ebase, uint32_t rank) {
        asm volatile("{.reg .pred p; setp.lt.u32 p, %3, %4; @p st.shared.u32 [%0], %1; @p st.shared.u32 [%0+%5], %2;}"
                     :: "r"(sb + SM_LS + (x & 31) * (kCapW * 4) + rank * 4), "r"(w0 & 0x7FFFu),
                        "r"(((w0 >> 15) + ebase) | ((x << 23) & 0x70000000u)), "r"(rank), "n"(kCapW), "n"(kLQ) : "memory");
    };
    unsigned spin = 0;
    if (warp == kWarps - 1) {
#pragma unroll
        for (int r = 0; r < 17; r++) {
            const uint32_t w = lds32(sb + SM_WE + (128 + r) * 128 + (((feat(2 * lane) >> 1) ^ ((r & 7) << 2)) << 2));
            sts32(sb + SM_W3 + r * 128 + ((lane ^ ((r & 7) << 2)) << 2), bf2h(hmul2(w, 0x3F003F00u)));
        }
        asm volatile("bar.sync 1, 288;" ::: "memory");
        if (lane == 0) {
            asm volatile("fence.acq_rel.gpu;" ::: "memory");
            asm volatile("st.relaxed.gpu.global.u16 [%0], %1;" :: "l"((unsigned short*)g_flag0 + cta), "h"((unsigned short)(tag | (lds32(sb + SM_MISC) >> 23))) : "memory");
        }
        __syncwarp();
        TSTAMP(2);
        if (PS) __nanosleep(PS);
        const uint32_t tag2 = (tag & 0xFF00u) * 0x10001u;
        uint4 v;
        do {
            asm volatile("ld.acquire.gpu.global.v4.u32 {%0,%1,%2,%3}, [%4];" : "=r"(v.x), "=r"(v.y), "=r"(v.z), "=r"(v.w) : "l"(g_flag0 + min(lane, 16)) : "memory");
            if (lane >= 16) v.z = v.w = v.x;
            v.x ^= tag2; v.y ^= tag2; v.z ^= tag2; v.w ^= tag2;
            if (++spin > kSpinLimit) __trap();
        } while ((v.x | v.y | v.z | v.w) & 0xFF00FF00u);
        uint32_t mx = __vmaxu2(__vmaxu2(v.x, v.y), __vmaxu2(v.z, v.w));
        mx = max(mx & 255, mx >> 16);
        mx = __reduce_max_sync(~0u, mx);
        if (lane == 0) sts32(sb + SM_MISC + 4, mx);
        TSTAMP(4);
    } else {
        const uint4* recp = g_rec + (warp * kG + cta) * 32 + (lane ^ (cta & 7));
        while ((hdr ^ (epoch << 26)) >> 26) {
            asm volatile("ld.relaxed.gpu.global.u32 %0, [%1];" : "=r"(hdr) : "l"(hdrp) : "memory");
            if (++spin > kSpinLimit) __trap();
        }
        hdr = lane * kCol + warp < kG ? hdr & 0x3FFFFFFu : 0u;
        uint4 rv[kSegPerWarp];
        uint32_t cnt[kSegPerWarp];
#pragma unroll
        for (int s = 0; s < kSegPerWarp; s++) {
            cnt[s] = __shfl_sync(~0u, hdr, s) & 0x1FFF;
            rv[s] = make_uint4(0, tag, 0, tag);
            if (2 * lane < cnt[s]) rv[s] = ld_relaxed(recp + s * (kCol * kG * 32));
        }
        if (lane < kSegPerWarp) sts32(sb + SM_SEG + (lane * kCol + warp) * 4, hdr);
        const int ms = 31 - __clz(__ballot_sync(~0u, (hdr & 0x1FFF) > 64)), more = ms < 0 ? -1 : ms * kCol + warp;
        uint4 ov = make_uint4(0, 0, 0, 0);
        if (ms >= 0 && lane < (__shfl_sync(~0u, hdr, ms) >> 13)) ov = ld_relaxed(g_ovf + more * kChunk + lane);
        if (warp < 8) {
            put_table(tw, warp, lane, nbase, ncta);
            asm volatile("bar.arrive 1, 288;" ::: "memory");
        }
        uint32_t rk[2][2];
#pragma unroll
        for (int s = 0; s <= kSegPerWarp; s++) {
            if (s < kSegPerWarp) {
                while (__any_sync(~0u, (rv[s].y ^ tag) >= 256 || ((rv[s].w ^ tag) >= 256 && 2 * lane + 1 < cnt[s]))) {
                    if (2 * lane < cnt[s]) rv[s] = ld_relaxed(recp + s * (kCol * kG * 32));
                    if (++spin > kSpinLimit) __trap();
                }
                if (s == 0) TSTAMP(9);
                rk[s & 1][0] = atoms_inc_lt(sb + SM_WCNT + (rv[s].y & 31) * 4, 2 * lane, cnt[s]);
                rk[s & 1][1] = atoms_inc_lt(sb + SM_WCNT + (rv[s].w & 31) * 4, 2 * lane + 1, cnt[s]);
            }
            if (s > 0) {
                place(rv[s - 1].x, rv[s - 1].y, ((s - 1) * kCol + warp) * kChunk, rk[~s & 1][0]);
                place(rv[s - 1].z, rv[s - 1].w, ((s - 1) * kCol + warp) * kChunk, rk[~s & 1][1]);
            }
        }
        TSTAMP(5);
        __syncwarp();
        for (int b = more; b >= 0; b -= kCol) {
            const uint32_t sg = lds32(sb + SM_SEG + b * 4);
            if ((sg & 0x1FFF) <= 64) continue;
            for (uint32_t i = lane; i < (sg >> 13); i += 32) {
                while (((ov.y ^ tag) | (ov.w ^ tag)) >= 256) {
                    ov = ld_relaxed(g_ovf + b * kChunk + i);
                    if (++spin > kSpinLimit) __trap();
                }
                if (ov.z == cta) place(ov.x, ov.y, b * kChunk, atoms_inc(sb + SM_WCNT + (ov.y & 31) * 4));
                ov.y = 0;
            }
            ov.y = 0;
        }
        TSTAMP(10);
    }
    uint32_t aw[4][4], w3[4][4];
    uint32_t wx[4];
#pragma unroll
    for (int j = 0; j < 4; j++) wx[j] = bf2h(lds16(sb + SM_WX + feat(16 * j + g) * 2) | (lds16(sb + SM_WX + feat(16 * j + 8 + g) * 2) << 16));
    cp_wait<0>();
    __syncthreads();
    TSTAMP(6);

    if (tid == 0) g_epoch[cta] = epoch;

    int w2;
    {
        const uint32_t key = (lds32(sb + SM_WCNT + lane * 4) << 5) | lane;
        const int r1 = __popc(__ballot_sync(~0u, key < __shfl_sync(~0u, key, warp)) & 0xFFFFu);
        const uint32_t key2 = __shfl_sync(~0u, key, lane | 16);
        int r2 = 0;
#pragma unroll
        for (int j = 0; j < 8; j++) r2 += __shfl_sync(~0u, key, 16 + ((lane >> 4) << 3) + j) > key2;
        r2 += __shfl_xor_sync(~0u, r2, 16);
        w2 = __ffs(__ballot_sync(~0u, r2 == r1)) - 1;
        const int k = lane & 7, j = lane < 16 ? k : 8 + (k >> 1);
        const int r = j < 6 ? warp + 32 * j : w2 + 16 + 32 * (j - 6), u = (lane >> 3) & 1, r3 = 1 + k + ((lane >> 4) << 3);
        const uint32_t a = lane >= 16 && (k & 1) ? sb + SM_W3 + (u << 4) : sb + SM_A + r * 128 + ((u ^ ((r + (r >> 5)) & 7)) << 4);
#pragma unroll
        for (int i = 0; i < 4; i++) {
            ldsm4t(aw[i], a ^ (i << 5));
            ldsm4t(w3[i], (sb + SM_W3 + r3 * 128 + ((u ^ (r3 & 7)) << 4)) ^ (i << 5));
        }
    }
    const uint32_t lsb = sb + SM_LS + warp * (kCapW * 4);
    const uint32_t stb = sb + SM_STAGE + warp * kStageBytes;
    const int lx = lane ^ ((lane >> 1) & 4) ^ (lane >> 4);
    const uint32_t cpB_ = stb + (lx << 4);
    const uint32_t ldB_ = stb + g * 128 + ((t ^ ((g & 1) << 2) ^ (g >> 1)) << 4);
    const uint32_t ldT_ = stb + ((lane & 7) + ((lane >> 4) << 3)) * 128 + ((((lane >> 3) & 1) ^ ((lane & 1) << 2) ^ ((lane >> 1) & 3)) << 4);
    const uint32_t ldE_ = stb + 2048 + ((lane & 7) + ((lane >> 4) << 3)) * 32 + ((((lane >> 3) ^ (lane >> 2)) & 1) << 4);
    uint32_t ohb = (lane & 8) ? sb + SM_POS + warp * kPosStride : sb + SM_OH;
    const uint32_t tabo = (lane & 7) << 4, eao = ((lx ^ (lane >> 3)) & 1) << 4;
    uint64_t tabp = (uint64_t)__cvta_generic_to_global(g_tab) + tabo;
    uint64_t eap = (uint64_t)__cvta_generic_to_global(e_attr) + eao;
    sts128(stb + 1024 + lane * 16, (uint32_t)tabp, (uint32_t)(tabp >> 32), (uint32_t)eap, (uint32_t)(eap >> 32));
    asm volatile("ld.volatile.shared.v2.u64 {%0,%1}, [%2];" : "=l"(tabp), "=l"(eap) : "r"(stb + 1024 + lane * 16) : "memory");
    sts128(stb + 512 + lane * 16, wx[0], wx[1], wx[2], wx[3]);
    { const uint4 w = lds128v(stb + 512 + lane * 16); wx[0] = w.x; wx[1] = w.y; wx[2] = w.z; wx[3] = w.w; }
    sts128(stb + lane * 16, cpB_, cpB_ ^ 32, ldB_, ldE_);
    sts128(stb + 1536 + lane * 16, ldT_, ldT_ ^ 32, ldT_ ^ 64, ldT_ ^ 96);
    const uint4 ad = lds128v(stb + lane * 16), at = lds128v(stb + 1536 + lane * 16);
    const uint32_t cpB = ad.x, cpB2 = ad.y, ldB = ad.z, ldE = ad.w, ldT[4] = {at.x, at.y, at.z, at.w};
    float acc[4][4], accp[4];
#pragma unroll
    for (int i = 0; i < 4; i++) { acc[i][0] = acc[i][1] = acc[i][2] = acc[i][3] = 0.f; accp[i] = 0.f; }
    auto switch_window = [&]() {
        __syncwarp();
        const int lane = fresh_lane();
        sts128(lsb + lane * 16, pack_bf16(acc[0][0], acc[0][1]), pack_bf16(acc[0][2], acc[0][3]), pack_bf16(acc[1][0], acc[1][1]), pack_bf16(acc[1][2], acc[1][3]));
        sts128(lsb + 512 + lane * 16, pack_bf16(acc[2][0], acc[2][1]), pack_bf16(acc[2][2], acc[2][3]), pack_bf16(acc[3][0], acc[3][1]), pack_bf16(acc[3][2], acc[3][3]));
        sts32(lsb + kLQ + lane * 4, pack_bf16(128.f * accp[0], 128.f * accp[1]));
#pragma unroll
        for (int i = 0; i < 4; i++) { acc[i][0] = acc[i][1] = acc[i][2] = acc[i][3] = 0.f; accp[i] = 0.f; }
#pragma unroll
        for (int j = 0; j < 3; j++) {
            const int r = j * 4 + (lane >> 3), hi = r < 6 ? r : r - 6, c = lane & 7, dloc = (r < 6 ? warp : 16 + w2) + 32 * hi;
            const bool ok = dloc < ncta;
            cp16z((r < 6 ? lsb + kLQ + 128 : sb + SM_H2 + warp * 768) + hi * 128 + ((c ^ hi) << 4), (const uint4*)h + (size_t)(ok ? nbase + dloc : 0) * 8 + c, ok ? 0u : ~0u);
        }
        ohb = ((lane & 8) ? sb + SM_POS + w2 * kPosStride : sb + SM_OH) + 128;
    };
    uint32_t pS, pQ, pD, qd;
    auto issue = [&](int lo, int st, bool on) {
        const uint4 s4 = lds128(pS + lo);
        const uint32_t q = lds32(pQ + lo);
        cp16g<128>(cpB + st, tabp, s4.x, on);
        cp16g<128>(cpB2 + st + 512, tabp, s4.y, on);
        cp16g<128>(cpB + st + 1024, tabp, s4.z, on);
        cp16g<128>(cpB2 + st + 1536, tabp, s4.w, on);
        cp16g<32>(cpB + st + 2048, eap, q & 0xFFFFFFu, on);
        cp_commit();
    };
    auto tile = [&](int sc, int lo, bool on) {
        const uint32_t oa = ohb + (qd >> 24);
        uint32_t oh[4], s0, s1;
        ldsm4(oh, oa);
        ldsm2t(s0, s1, oa + 256);
        cp_wait<2>();
        __syncwarp();
        uint32_t ef[4], pa, pb;
        const uint4 x0 = lds128(ldB + sc), x1 = lds128(ldB + sc + 1024);
        ldsm4(ef, ldE + sc);
        uint32_t c[4][4];
#pragma unroll
        for (int i = 0; i < 4; i++) ldsm4t(c[i], ldT[i] + sc);
#pragma unroll
        for (int i = 0; i < 4; i++) ef[i] = bf2h(ef[i]);
        const uint32_t d0 = hsub2(oh[3], __byte_perm(bitsel<0x003F003Fu>(bitsel<0x00070007u>(x0.x, x0.y << 3), x0.z << 6), 0, 0x2044));
        const uint32_t d1 = hsub2(oh[1], __byte_perm(bitsel<0x003F003Fu>(bitsel<0x00070007u>(x1.x, x1.y << 3), x1.z << 6), 0, 0x2044));
        const uint32_t q0 = bf2h(hmul2(d0, d0)), q1 = bf2h(hmul2(d1, d1));
        auto pre = [&](int i) {
            mma_h(c[i][0], c[i][1], w3[i], ef[0], ef[1]);
            mma_h(c[i][2], c[i][3], w3[i], ef[2], ef[3]);
            mma_h(c[i][0], c[i][1], aw[i], oh[0], q0);
            mma_h(c[i][2], c[i][3], aw[i], oh[2], q1);
        };
        auto act = [&](int i) {
#pragma unroll
            for (int q = 0; q < 4; q++) c[i][q] = silu_half2(c[i][q]);
            mma_f16(acc[i], c[i], s0, s1);
            pa = hfma2_hi(c[i][1], wx[i], hfma2_lo(c[i][0], wx[i], i ? pa : 0u));
            pb = hfma2_hi(c[i][3], wx[i], hfma2_lo(c[i][2], wx[i], i ? pb : 0u));
        };
        pre(0);
        pre(1);
        act(0);
        pre(2);
        act(1);
        pre(3);
        act(2);
        __syncwarp();
        qd = lds32(pD + lo + 64);
        issue(lo + 192, sc, on);
        act(3);
        float cs[4];
        mma_f16_k8_init(cs, movm(pa), movm(pb), 0x3C003C00u);
        const uint32_t cp = pack_bf16(cs[0], cs[2]);
        const uint32_t v0 = hmul2_lo(d0, cp), v1 = hmul2_hi(d1, cp);
        mma_bf16(accp, movm(v0), v0, movm(v1), v1, s0, s1);
    };
    bool synced = false;
    for (;;) {
        int sched, delta = 0;
        uint32_t first;
        __syncwarp();
        const int lane = fresh_lane();
        const uint32_t lsb2 = sb + SM_LS + (16 + w2) * (kCapW * 4);
        const uint32_t cnt0 = __reduce_max_sync(~0u, lds32(sb + SM_WCNT + warp * 4)), cnt1 = __reduce_max_sync(~0u, lds32(sb + SM_WCNT + 64 + w2 * 4));
        if (cnt0 <= kCapW && cnt1 <= kCapW) {
            const int n0 = (cnt0 + 15) >> 4, n1 = (cnt1 + 15) >> 4;
            const int i = (lane < 16 ? cnt0 : cnt1) + (lane & 15);
            const uint32_t a = (lane < 16 ? lsb : lsb2) + i * 4;
            if (i < 16 * (lane < 16 ? n0 : n1)) { sts32(a, nbase); sts32(a + kLQ, kPadQ | e0); }
            first = lsb; sched = n0 | ((n0 + n1) << 8); delta = lsb2 - lsb - 64 * n0;
            sched |= 1 << 29;
        } else {
            const uint32_t cur = __reduce_max_sync(~0u, lds32(sb + SM_CUR + warp * 4));
            int n = 0, cur_win = cur >> 24, cur_seg = (cur >> 16) & 255, cur_pos = cur & 0xFFFF;
            while (cur_seg < kG && n <= kCapW - 48) {
                const uint32_t sg = __reduce_max_sync(~0u, lds32(sb + SM_SEG + cur_seg * 4));
                const int len = 64 + ((sg & 0x1FFF) > 64 ? sg >> 13 : 0), i = cur_pos + lane;
                uint2 v = make_uint2(0, 255);
                if (i < 64) { if (i < (int)(sg & 0x1FFF)) v = __ldcg((const uint2*)g_rec + (cur_seg * kG + cta) * 64 + (i ^ ((2 * cta) & 14))); }
                else if (i < len) {
                    const uint4 o = __ldcg(g_ovf + cur_seg * kChunk + i - 64);
                    if (o.z == cta) v = make_uint2(o.x, o.y);
                }
                const bool hit = (v.y & 255) != 255 && (int)(v.y & 31) == (cur_win ? 16 + w2 : warp);
                const uint32_t bal = __ballot_sync(~0u, hit);
                if (hit) {
                    const int k = n + __popc(bal & ((1u << lane) - 1));
                    sts32(lsb2 + k * 4, v.x & 0x7FFFu);
                    sts32(lsb2 + kLQ + k * 4, ((v.x >> 15) + cur_seg * kChunk) | ((v.y << 23) & 0x70000000u));
                }
                n += __popc(bal);
                cur_pos += 32;
                if (cur_pos >= len) { cur_pos = 0; cur_seg++; }
            }
            if (lane < 16) { sts32(lsb2 + (n + lane) * 4, nbase); sts32(lsb2 + kLQ + (n + lane) * 4, kPadQ | e0); }
            const int nt = (n + 15) >> 4;
            first = lsb2; sched = 255 | (nt << 8);
            uint32_t nxt = (cur_win << 24) | (cur_seg << 16) | cur_pos;
            if (cur_seg == kG) {
                if (cur_win == 0) { sched = nt | (nt << 8); nxt = 1u << 24; } else sched |= 1 << 29;
            }
            __syncwarp();
            if (lane == 0) sts32(sb + SM_CUR + warp * 4, nxt);
        }
        __syncwarp();
        pS = first + (lane >> 3) * 16;
        const int pe = (lane ^ ((lane >> 1) & 4)) >> 1, pd = (lane ^ ((lane >> 1) & 8)) & 15;
        pQ = first + kLQ + (4 * (pe & 3) + (pe >> 2)) * 4;
        pD = first + kLQ + (4 * (pd & 3) + (pd >> 2)) * 4;
        sched = __reduce_max_sync(~0u, sched);
        const int n0 = (int8_t)sched * 64, nt = ((sched >> 8) & 255) * 64, ntm = __reduce_max_sync(~0u, nt - 192);
        if (n0 == 0) { pS += delta; pQ += delta; pD += delta; }
        issue(0, 0, nt > 0);
        qd = lds32(pD);
        if (n0 == 64) { pS += delta; pQ += delta; }
        issue(64, kStageStride, nt > 64);
        if (!synced) { __syncthreads(); synced = true; }
        if (n0 == 128) { pS += delta; pQ += delta; }
        issue(128, 2 * kStageStride, nt > 128);
        int sc = 0, ev = 0;
#pragma unroll 1
        for (int lo = 0;; lo += 64) {
            if (__builtin_expect(lo == ev, 0)) {
                if (lo == n0 - 192) { pS += delta; pQ += delta; }
                if (lo == n0 - 64) pD += delta;
                if (lo == n0) switch_window();
                if (lo == nt) break;
                ev = lo < n0 - 192 ? n0 - 192 : lo < n0 ? lo + 64 : nt;
            }
            tile(sc, lo, lo < ntm);
            sc = sc == 2 * kStageStride ? 0 : sc + kStageStride;
        }
        if (sched & (1 << 29)) break;
    }
    TSTAMP(7);

    {
        const int lane = fresh_lane(), g = lane >> 2, t = lane & 3;
        uint4 ma = lds128(lsb + lane * 16), mb = lds128(lsb + 512 + lane * 16);
        {
            uint32_t z = hadd2(hadd2(hadd2(ma.x, ma.y), hadd2(ma.z, ma.w)), hadd2(hadd2(mb.x, mb.y), hadd2(mb.z, mb.w)));
            z = hadd2(z, lds32(lsb + kLQ + lane * 4));
            float f = accp[0] + accp[1];
#pragma unroll
            for (int i = 0; i < 4; i++) f += (acc[i][0] + acc[i][1]) + (acc[i][2] + acc[i][3]);
            f += __uint_as_float(z << 16) + __uint_as_float(z & 0xFFFF0000u);
            if (__any_sync(~0u, !(fabsf(f) < __int_as_float(0x7F800000)) || lds32(sb + SM_MISC + 4) >= 127 + 15)) {
                float* buf = (float*)(smem + SM_STAGE + kStageStride + warp * kStageBytes);
#pragma unroll 1
                for (int sub = 0; sub < 2; sub++) {
                    exact_window(h, pos, e_attr, w_e, w_x, (const uint32_t*)(smem + SM_SEG), buf, sub ? 16 + w2 : warp);
#pragma unroll
                    for (int i = 0; i < 4; i++)
#pragma unroll
                        for (int q = 0; q < 4; q++) acc[i][q] = t < 3 ? buf[(2 * t + (q & 1)) * 64 + feat(16 * i + 8 * (q >> 1) + g)] : 0.f;
                    accp[0] = t < 3 ? buf[384 + 8 * t + (g >> 1)] * (1.f / 128.f) : 0.f;
                    accp[1] = t < 3 ? buf[388 + 8 * t + (g >> 1)] * (1.f / 128.f) : 0.f;
                    if (sub == 0) switch_window();
                    __syncwarp();
                }
                ma = lds128(lsb + lane * 16); mb = lds128(lsb + 512 + lane * 16);
            }
        }
        const uint32_t m0[4][2] = {{ma.x, ma.y}, {ma.z, ma.w}, {mb.x, mb.y}, {mb.z, mb.w}};
        float c[8][4];
#pragma unroll
        for (int j = 0; j < 8; j++) { c[j][0] = c[j][1] = c[j][2] = c[j][3] = 0.f; }
        uint32_t hf[4][4];
#pragma unroll
        for (int kk = 0; kk < 8; kk++) {
            const int ks = kk ^ 4;
            uint32_t a[4];
            if (ks < 4) {
                if (ks == 0) { cp_commit(); cp_wait<0>(); __syncwarp(); }
                const int hi = min(lane & 7, 5);
                ldsm4(hf[ks], ((lane & 8) ? sb + SM_H2 + warp * 768 : lsb + kLQ + 128) + hi * 128 + (((2 * ks + (lane >> 4)) ^ hi) << 4));
                a[0] = hf[ks][0]; a[1] = hf[ks][1]; a[2] = hf[ks][2]; a[3] = hf[ks][3];
            } else {
                const int i = ks - 4;
                a[0] = movm(m0[i][0]);
                a[1] = movm(pack_bf16(acc[i][0], acc[i][1]));
                a[2] = movm(m0[i][1]);
                a[3] = movm(pack_bf16(acc[i][2], acc[i][3]));
            }
#pragma unroll
            for (int i = 0; i < 4; i++) {
                uint32_t w[4];
                const int k = 16 * ks + (lane & 7) + ((lane >> 4) << 3);
                ldsm4t(w, sb + SM_WH + k * 128 + (((2 * i + ((lane >> 3) & 1)) ^ (k & 7)) << 4));
                mma_bf16(c[2 * i], a[0], a[1], a[2], a[3], w[0], w[2]);
                mma_bf16(c[2 * i + 1], a[0], a[1], a[2], a[3], w[1], w[3]);
            }
            if (kk == 3 && (g & 1) && g < 6 && t < 3) {
                const uint32_t dl[2] = {lds32(lsb + kLQ + lane * 4), pack_bf16(128.f * accp[0], 128.f * accp[1])};
#pragma unroll
                for (int sub = 0; sub < 2; sub++) {
                    const uint32_t pa = sb + SM_POS + (sub ? w2 : warp) * kPosStride + sub * 128 + t * 32 + (g >> 1) * 4;
                    const uint32_t o = hadd2(__byte_perm(lds32(pa), lds32(pa + 16), 0x7632), dl[sub]);
                    const int dloc = (sub ? 16 + w2 : warp) + 64 * t;
                    unsigned short* op = (unsigned short*)out_pos + (size_t)(nbase + dloc) * 3 + (g >> 1);
                    if (dloc < ncta) op[0] = (unsigned short)o;
                    if (dloc + 32 < ncta) op[96] = (unsigned short)(o >> 16);
                }
            }
        }
        __syncwarp();
#pragma unroll
        for (int ks = 0; ks < 4; ks++) {
            uint32_t o[4];
#pragma unroll
            for (int q = 0; q < 4; q++) {
                const float* cc = c[2 * ks + (q >> 1)] + 2 * (q & 1);
                o[q] = hadd2(hf[ks][q], pack_bf16(silu_half(0.5f * cc[0]), silu_half(0.5f * cc[1])));
            }
            const int r = lane & 15;
            stsm4(stb + r * 128 + (((2 * ks + (lane >> 4)) ^ (r & 7)) << 4), o[0], o[1], o[2], o[3]);
        }
        __syncwarp();
#pragma unroll
        for (int j = 0; j < 4; j++) {
            const int r = j * 4 + (lane >> 3), cc = lane & 7, dloc = (j < 2 ? warp : 16 + w2) + 32 * (r & 7);
            const uint4 v = lds128(stb + r * 128 + ((cc ^ (r & 7)) << 4));
            if (dloc < ncta) ((uint4*)out_h)[(size_t)(nbase + dloc) * 8 + cc] = v;
        }
    }
    TSTAMP(8);
}

}

extern "C" void kernel_launch(void* const* d_in, const int* in_sizes, int n_in, void* d_out, int out_size) {
    static bool init = false;
    if (!init) {
        cudaFuncSetAttribute(egnn_kernel, cudaFuncAttributeMaxDynamicSharedMemorySize, SM_TOTAL);
        init = true;
    }
    __nv_bfloat16* out = (__nv_bfloat16*)d_out;
    egnn_kernel<<<kG, kThreads, SM_TOTAL>>>(
        (const __nv_bfloat16*)d_in[0], (const __nv_bfloat16*)d_in[1], (const __nv_bfloat16*)d_in[2],
        (const int*)d_in[3], (const int*)d_in[4], (const __nv_bfloat16*)d_in[5],
        (const __nv_bfloat16*)d_in[6], (const __nv_bfloat16*)d_in[7], out, out + (size_t)kN * 64);
}
```

```cpp
#include <cuda_runtime.h>
#include <cuda_bf16.h>
#include <cuda_fp16.h>
#include <stdint.h>

namespace {

constexpr int kN = 25000;
constexpr int kE = 800000;
constexpr int kG = 132;
constexpr int kNPC = 190;
constexpr int kChunk = 6064;
constexpr int kThreads = 512;
constexpr int kWarps = 16;
constexpr int kCapW = 272;
constexpr int kStageBytes = 2560;
constexpr int kStageStride = kWarps * kStageBytes;
constexpr int kSegPerWarp = 9;
constexpr int kCol = kWarps - 1;
constexpr int kPosStride = 528;
constexpr uint32_t kBinMul = 22605092u;
constexpr unsigned kSpinLimit = 1u << 22;
constexpr uint32_t kPadQ = 6u << 28;

constexpr int SM_STAGE = 0;
constexpr int SM_REC = SM_STAGE;
constexpr int SM_WE = SM_STAGE + kG * 512;
constexpr int SM_H = SM_WE + 145 * 128;
constexpr int SM_A = SM_H + 192 * 128;
constexpr int SM_W3 = SM_A - 17 * 128;
constexpr int SM_H2 = SM_STAGE + 3 * kStageStride;
constexpr int SM_LS = SM_A + 192 * 128;
constexpr int kLQ = kWarps * 2 * kCapW * 4;
constexpr int SM_WH = SM_LS + 2 * kLQ;
constexpr int SM_POS = SM_WH + 16384;
constexpr int SM_OH = SM_POS + kWarps * kPosStride;
constexpr int SM_WX = SM_OH + 512;
constexpr int SM_HIST = SM_WX + 128;
constexpr int SM_WCNT = SM_HIST + 144 * 4;
constexpr int SM_MISC = SM_WCNT + 32 * 4;
constexpr int SM_CUR = SM_MISC + 32;
constexpr int SM_SEG = SM_CUR + 64;
constexpr int SM_TOTAL = SM_SEG + 144 * 4;
static_assert(SM_W3 >= 2 * kStageStride && SM_LS >= SM_H2 + kWarps * 768, "aliasing");
static_assert(SM_TOTAL <= 232448, "shared memory");

__device__ uint4 g_tab[kG * kNPC * 8];
__device__ uint4 g_rec[kG * kG * 32];
__device__ uint4 g_ovf[kG * kChunk];
__device__ uint4 g_flag0[17];
__device__ __align__(128) unsigned g_hdr[kG * 160];
__device__ unsigned g_epoch[kG];
#define TDEP(i, x)
#define TSTAMP(i)

__device__ __forceinline__ void mma_bf16(float (&c)[4], uint32_t a0, uint32_t a1, uint32_t a2, uint32_t a3, uint32_t b0, uint32_t b1) {
    asm volatile("mma.sync.aligned.m16n8k16.row.col.f32.bf16.bf16.f32 {%0,%1,%2,%3}, {%4,%5,%6,%7}, {%8,%9}, {%0,%1,%2,%3};"
        : "+f"(c[0]), "+f"(c[1]), "+f"(c[2]), "+f"(c[3]) : "r"(a0), "r"(a1), "r"(a2), "r"(a3), "r"(b0), "r"(b1));
}
__device__ __forceinline__ void mma_f16(float (&c)[4], const uint32_t (&a)[4], uint32_t b0, uint32_t b1) {
    asm volatile("mma.sync.aligned.m16n8k16.row.col.f32.f16.f16.f32 {%0,%1,%2,%3}, {%4,%5,%6,%7}, {%8,%9}, {%0,%1,%2,%3};"
        : "+f"(c[0]), "+f"(c[1]), "+f"(c[2]), "+f"(c[3]) : "r"(a[0]), "r"(a[1]), "r"(a[2]), "r"(a[3]), "r"(b0), "r"(b1));
}
__device__ __forceinline__ void mma_h(uint32_t& c0, uint32_t& c1, const uint32_t (&a)[4], uint32_t b0, uint32_t b1) {
    asm volatile("mma.sync.aligned.m16n8k16.row.col.f16.f16.f16.f16 {%0,%1}, {%2,%3,%4,%5}, {%6,%7}, {%0,%1};"
        : "+r"(c0), "+r"(c1) : "r"(a[0]), "r"(a[1]), "r"(a[2]), "r"(a[3]), "r"(b0), "r"(b1));
}
__device__ __forceinline__ void mma_f16_k8_init(float (&c)[4], uint32_t a0, uint32_t a1, uint32_t b0) {
    asm volatile("mma.sync.aligned.m16n8k8.row.col.f32.f16.f16.f32 {%0,%1,%2,%3}, {%4,%5}, {%6}, {%7,%7,%7,%7};"
        : "=f"(c[0]), "=f"(c[1]), "=f"(c[2]), "=f"(c[3]) : "r"(a0), "r"(a1), "r"(b0), "f"(0.f));
}
__device__ __forceinline__ uint32_t movm(uint32_t a) {
    uint32_t d; asm("movmatrix.sync.aligned.m8n8.trans.b16 %0, %1;" : "=r"(d) : "r"(a)); return d;
}
__device__ __forceinline__ void ldsm4(uint32_t (&r)[4], uint32_t a) {
    asm volatile("ldmatrix.sync.aligned.m8n8.x4.shared.b16 {%0,%1,%2,%3}, [%4];" : "=r"(r[0]), "=r"(r[1]), "=r"(r[2]), "=r"(r[3]) : "r"(a));
}
__device__ __forceinline__ void ldsm4t(uint32_t (&r)[4], uint32_t a) {
    asm volatile("ldmatrix.sync.aligned.m8n8.x4.trans.shared.b16 {%0,%1,%2,%3}, [%4];" : "=r"(r[0]), "=r"(r[1]), "=r"(r[2]), "=r"(r[3]) : "r"(a));
}
__device__ __forceinline__ void stsm4(uint32_t a, uint32_t r0, uint32_t r1, uint32_t r2, uint32_t r3) {
    asm volatile("stmatrix.sync.aligned.m8n8.x4.shared.b16 [%0], {%1,%2,%3,%4};" :: "r"(a), "r"(r0), "r"(r1), "r"(r2), "r"(r3) : "memory");
}
__device__ __forceinline__ uint4 lds128(uint32_t a) {
    uint4 v; asm volatile("ld.shared.v4.u32 {%0,%1,%2,%3}, [%4];" : "=r"(v.x), "=r"(v.y), "=r"(v.z), "=r"(v.w) : "r"(a)); return v;
}
__device__ __forceinline__ uint4 lds128v(uint32_t a) {
    uint4 v; asm volatile("ld.volatile.shared.v4.u32 {%0,%1,%2,%3}, [%4];" : "=r"(v.x), "=r"(v.y), "=r"(v.z), "=r"(v.w) : "r"(a) : "memory"); return v;
}
__device__ __forceinline__ uint32_t lds32(uint32_t a) {
    uint32_t v; asm volatile("ld.shared.u32 %0, [%1];" : "=r"(v) : "r"(a)); return v;
}
__device__ __forceinline__ uint32_t lds16(uint32_t a) {
    uint32_t v; asm volatile("ld.shared.u16 %0, [%1];" : "=r"(v) : "r"(a)); return v;
}
__device__ __forceinline__ void sts32(uint32_t a, uint32_t v) { asm volatile("st.shared.u32 [%0], %1;" :: "r"(a), "r"(v) : "memory"); }
__device__ __forceinline__ void sts64(uint32_t a, uint32_t x, uint32_t y) { asm volatile("st.shared.v2.u32 [%0], {%1,%2};" :: "r"(a), "r"(x), "r"(y) : "memory"); }
__device__ __forceinline__ uint32_t atoms_inc(uint32_t a) {
    uint32_t v; asm volatile("atom.shared.add.u32 %0, [%1], 1;" : "=r"(v) : "r"(a) : "memory"); return v;
}
__device__ __forceinline__ uint32_t atoms_inc_lt(uint32_t a, uint32_t i, uint32_t n) {
    uint32_t v; asm volatile("{.reg .pred p; setp.lt.u32 p, %2, %3; mov.b32 %0, -1; @p atom.shared.add.u32 %0, [%1], 1;}" : "=r"(v) : "r"(a), "r"(i), "r"(n) : "memory"); return v;
}
__device__ __forceinline__ void cp16(uint32_t d, const void* s) {
    asm volatile("cp.async.cg.shared.global [%0], [%1], 16;" :: "r"(d), "l"(s) : "memory");
}
__device__ __forceinline__ void cp16z(uint32_t d, const void* s, uint32_t flag) {
    asm volatile("{.reg .pred p; setp.lt.s32 p, %2, 0; cp.async.cg.shared.global [%0], [%1], 16, p;}" :: "r"(d), "l"(s), "r"(flag) : "memory");
}
__device__ __forceinline__ void cp_commit() { asm volatile("cp.async.commit_group;" ::: "memory"); }
template <int n> __device__ __forceinline__ void cp_wait() { asm volatile("cp.async.wait_group %0;" :: "n"(n) : "memory"); }
__device__ __forceinline__ int4 ldg_stream(const int4* p) {
    int4 v; asm volatile("ld.relaxed.gpu.global.v4.s32 {%0,%1,%2,%3}, [%4];" : "=r"(v.x), "=r"(v.y), "=r"(v.z), "=r"(v.w) : "l"(p) : "memory"); return v;
}
__device__ __forceinline__ uint32_t ldg16(const unsigned short* p) {
    uint32_t v; asm volatile("ld.relaxed.gpu.global.u16 %0, [%1];" : "=r"(v) : "l"(p) : "memory"); return v;
}
__device__ __forceinline__ uint32_t pack_bf16(float lo, float hi) {
    uint32_t d; asm("cvt.rn.bf16x2.f32 %0, %1, %2;" : "=r"(d) : "f"(hi), "f"(lo)); return d;
}
__device__ __forceinline__ uint32_t pack_f16(float lo, float hi) {
    uint32_t d; asm("cvt.rn.f16x2.f32 %0, %1, %2;" : "=r"(d) : "f"(hi), "f"(lo)); return d;
}
__device__ __forceinline__ uint32_t hmul2(uint32_t a, uint32_t b) { uint32_t d; asm("mul.rn.bf16x2 %0, %1, %2;" : "=r"(d) : "r"(a), "r"(b)); return d; }
__device__ __forceinline__ uint32_t hsub2(uint32_t a, uint32_t b) { uint32_t d; asm("sub.rn.bf16x2 %0, %1, %2;" : "=r"(d) : "r"(a), "r"(b)); return d; }
__device__ __forceinline__ uint32_t hadd2(uint32_t a, uint32_t b) { uint32_t d; asm("add.rn.bf16x2 %0, %1, %2;" : "=r"(d) : "r"(a), "r"(b)); return d; }
__device__ __forceinline__ float silu_half(float x) {
    float t; asm volatile("tanh.approx.f32 %0, %1;" : "=f"(t) : "f"(x)); return fmaf(x, t, x);
}
__device__ __forceinline__ uint32_t silu_half2(uint32_t x) {
    uint32_t d; asm volatile("{.reg .b32 t; tanh.approx.f16x2 t, %1; fma.rn.f16x2 %0, %1, t, %1;}" : "=r"(d) : "r"(x)); return d;
}
__device__ __forceinline__ uint32_t bf2h(uint32_t x) { return pack_f16(__uint_as_float(x << 16), __uint_as_float(x & 0xFFFF0000u)); }
__device__ __forceinline__ int feat(int p) { return (p & 33) | ((p & 6) << 2) | ((p >> 2) & 6); }
__device__ __forceinline__ void ldsm2t(uint32_t& r0, uint32_t& r1, uint32_t a) {
    asm volatile("ldmatrix.sync.aligned.m8n8.x2.trans.shared.b16 {%0,%1}, [%2];" : "=r"(r0), "=r"(r1) : "r"(a));
}
__device__ __forceinline__ void sts128(uint32_t a, uint32_t x, uint32_t y, uint32_t z, uint32_t w) {
    asm volatile("st.shared.v4.u32 [%0], {%1,%2,%3,%4};" :: "r"(a), "r"(x), "r"(y), "r"(z), "r"(w) : "memory");
}
template <int mul> __device__ __forceinline__ void cp16g(uint32_t d, uint64_t base, uint32_t idx, bool p) {
    asm volatile("{.reg .pred p; .reg .b64 a; setp.ne.u32 p, %3, 0; mul.wide.u32 a, %2, %4; add.s64 a, a, %1; @p cp.async.cg.shared.global [%0], [a], 16;}"
                 :: "r"(d), "l"(base), "r"(idx), "r"((uint32_t)p), "n"(mul) : "memory");
}
template <uint32_t m> __device__ __forceinline__ uint32_t bitsel(uint32_t a, uint32_t b) {
    uint32_t d; asm("lop3.b32 %0, %1, %2, %3, 0xE2;" : "=r"(d) : "r"(a), "n"(m), "r"(b)); return d;
}
__device__ __forceinline__ uint32_t hfma2_lo(uint32_t a, uint32_t b, uint32_t c) {
    uint32_t d; asm("{.reg .b16 l,h; .reg .b32 x; mov.b32 {l,h}, %2; mov.b32 x, {l,l}; fma.rn.f16x2 %0, %1, x, %3;}" : "=r"(d) : "r"(a), "r"(b), "r"(c)); return d;
}
__device__ __forceinline__ uint32_t hfma2_hi(uint32_t a, uint32_t b, uint32_t c) {
    uint32_t d; asm("{.reg .b16 l,h; .reg .b32 x; mov.b32 {l,h}, %2; mov.b32 x, {h,h}; fma.rn.f16x2 %0, %1, x, %3;}" : "=r"(d) : "r"(a), "r"(b), "r"(c)); return d;
}
__device__ __forceinline__ uint4 ld_relaxed(const uint4* p) {
    uint4 v; asm volatile("ld.relaxed.gpu.global.v4.u32 {%0,%1,%2,%3}, [%4];" : "=r"(v.x), "=r"(v.y), "=r"(v.z), "=r"(v.w) : "l"(p) : "memory"); return v;
}
__device__ __forceinline__ uint32_t ld_relaxed32(const unsigned* p) {
    uint32_t v; asm volatile("ld.relaxed.gpu.global.u32 %0, [%1];" : "=r"(v) : "l"(p) : "memory"); return v;
}
__device__ __forceinline__ void st_relaxed(uint4* p, uint32_t x, uint32_t y, uint32_t z, uint32_t w) {
    asm volatile("st.relaxed.gpu.global.v4.u32 [%0], {%1,%2,%3,%4};" :: "l"(p), "r"(x), "r"(y), "r"(z), "r"(w) : "memory");
}
__device__ __forceinline__ uint32_t hmul2_lo(uint32_t a, uint32_t b) {
    uint32_t d; asm("{.reg .b16 l,h; .reg .b32 x; mov.b32 {l,h}, %2; mov.b32 x, {l,l}; mul.rn.bf16x2 %0, %1, x;}" : "=r"(d) : "r"(a), "r"(b)); return d;
}
__device__ __forceinline__ uint32_t hmul2_hi(uint32_t a, uint32_t b) {
    uint32_t d; asm("{.reg .b16 l,h; .reg .b32 x; mov.b32 {l,h}, %2; mov.b32 x, {h,h}; mul.rn.bf16x2 %0, %1, x;}" : "=r"(d) : "r"(a), "r"(b)); return d;
}
template <int n> __device__ __forceinline__ uint32_t embed_bits(uint32_t w, uint32_t r) {
    constexpr uint32_t m = ((1u << n) - 1) * 0x10001u;
    r &= m;
    const uint32_t v = __vmaxu2((w & 0x7FFF7FFFu) + (0x10001u << (n - 1)), r) - r;
    return (v & ~m) | r | (w & 0x80008000u);
}

template <class F>
__device__ __forceinline__ uint32_t project(uint32_t sb, int warp, int lane, F hook, uint4 (&tw)[6]) {
    const int g = lane >> 2, t = lane & 3, row0 = (warp & 3) * 48, cg = warp >> 2;
    float c[3][4][4];
#pragma unroll
    for (int m = 0; m < 3; m++)
#pragma unroll
        for (int j = 0; j < 4; j++) { c[m][j][0] = c[m][j][1] = c[m][j][2] = c[m][j][3] = 0.f; }
    const uint32_t wa = sb + SM_WE + ((cg < 2 ? 64 : 0) + (lane & 7) + ((lane >> 4) << 3)) * 128 + (((4 * (cg & 1) + ((lane >> 3) & 1)) ^ (lane & 7)) << 4);
    const uint32_t ha = sb + SM_H + (row0 + (lane & 15)) * 128 + (((lane >> 4) ^ (lane & 7)) << 4);
#pragma unroll
    for (int ks = 0; ks < 4; ks++) {
        uint32_t w[2][4];
        ldsm4t(w[0], wa + ks * 2048);
        ldsm4t(w[1], (wa ^ 32) + ks * 2048);
#pragma unroll
        for (int m = 0; m < 3; m++) {
            uint32_t hf[4];
            ldsm4(hf, (ha ^ (ks << 5)) + m * 2048);
            hook(ks * 3 + m);
#pragma unroll
            for (int j = 0; j < 4; j++) mma_bf16(c[m][j], hf[0], hf[1], hf[2], hf[3], w[j >> 1][j & 1], w[j >> 1][2 + (j & 1)]);
        }
    }
    float mx = 0.f;
#pragma unroll
    for (int m = 0; m < 3; m++)
#pragma unroll
        for (int u = 0; u < 2; u++) {
            uint32_t wd[4];
#pragma unroll
            for (int j = 0; j < 4; j++) {
                mx = fmaxf(mx, fmaxf(fabsf(c[m][j][2 * u]), fabsf(c[m][j][2 * u + 1])));
                wd[j] = pack_f16(c[m][j][2 * u] * 0.5f, c[m][j][2 * u + 1] * 0.5f);
            }
            const int r = row0 + 16 * m;
            if (cg == 0) {
                const uint32_t p = __byte_perm(lds32(sb + SM_POS + (8 * u + g) * kPosStride + (r & 16) * 8 + (r >> 5) * 16 + 4 * t), 0, 0x4342);
                wd[0] = embed_bits<3>(wd[0], p);
                wd[1] = embed_bits<3>(wd[1], p >> 3);
                wd[2] = embed_bits<2>(wd[2], p >> 6);
            }
            tw[2 * m + u] = make_uint4(wd[0], wd[1], wd[2], wd[3]);
            if (cg >= 2) sts128(sb + SM_A + (r + 8 * u + g) * 128 + (((4 * (cg & 1) + t) ^ ((g + (r >> 5)) & 7)) << 4), wd[0], wd[1], wd[2], wd[3]);
        }
    return __float_as_uint(mx * 0.5f);
}

__device__ __forceinline__ void put_table(const uint4 (&tw)[6], int warp, int lane, int nbase, int ncta) {
    const int r = (warp & 3) * 48 + (lane >> 2);
#pragma unroll
    for (int i = 0; i < 6; i++)
        if (r + 8 * i < ncta) st_relaxed(g_tab + (size_t)(nbase + r + 8 * i) * 8 + (warp >> 2) * 4 + (lane & 3), tw[i].x, tw[i].y, tw[i].z, tw[i].w);
}
#define PD 2
__device__ __forceinline__ int fresh_lane() { int l; asm volatile("mov.u32 %0, %%laneid;" : "=r"(l)); return l; }

__device__ __noinline__ void exact_window(const __nv_bfloat16* h, const __nv_bfloat16* pos, const __nv_bfloat16* e_attr,
                                          const __nv_bfloat16* w_e, const __nv_bfloat16* w_x, const uint32_t* seg, float* buf, int win) {
    const int lane = threadIdx.x & 31, cta = blockIdx.x;
    auto rb = [](float x) { return __bfloat162float(__float2bfloat16(x)); };
    for (int i = lane; i < 6 * 68; i += 32) buf[i] = 0.f;
    __syncwarp();
    for (int b = 0; b < kG; b++) {
        const int cnt = seg[b] & 0x1FFF, len = cnt > 64 ? 64 + (seg[b] >> 13) : cnt;
        for (int i0 = 0; i0 < len; i0 += 32) {
            const int i = i0 + lane;
            uint2 v = make_uint2(0, 255);
            if (i < 64) { if (i < cnt) v = __ldcg((const uint2*)g_rec + (b * kG + cta) * 64 + (i ^ ((2 * cta) & 14))); }
            else if (i < len) {
                const uint4 o = __ldcg(g_ovf + b * kChunk + i - 64);
                if (o.z == cta) v = make_uint2(o.x, o.y);
            }
            for (uint32_t bal = __ballot_sync(~0u, (v.y & 255) != 255 && (int)(v.y & 31) == win); bal; bal &= bal - 1) {
                const uint32_t w0 = __shfl_sync(~0u, v.x, __ffs(bal) - 1), dl = __shfl_sync(~0u, v.y, __ffs(bal) - 1) & 255;
                const int sn = w0 & 0x7FFF, dn = cta * kNPC + dl, e = (w0 >> 15) + b * kChunk;
                float df[3], d2 = 0.f, p0 = 0.f, p1 = 0.f;
                for (int c = 0; c < 3; c++) {
                    df[c] = rb(__bfloat162float(pos[dn * 3 + c]) - __bfloat162float(pos[sn * 3 + c]));
                    d2 += rb(df[c] * df[c]);
                }
                for (int k = 0; k < 145; k++) {
                    const float x = k == 128 ? rb(d2) : __bfloat162float(k < 64 ? h[dn * 64 + k] : k < 128 ? h[sn * 64 + k - 64] : e_attr[(size_t)e * 16 + k - 129]);
                    p0 = fmaf(x, __bfloat162float(w_e[k * 64 + lane]), p0);
                    p1 = fmaf(x, __bfloat162float(w_e[k * 64 + 32 + lane]), p1);
                }
                p0 = rb(silu_half(0.5f * rb(p0)));
                p1 = rb(silu_half(0.5f * rb(p1)));
                float cs = p0 * __bfloat162float(w_x[lane]) + p1 * __bfloat162float(w_x[32 + lane]);
                for (int o = 16; o; o >>= 1) cs += __shfl_xor_sync(~0u, cs, o);
                buf[(dl >> 5) * 64 + lane] += p0;
                buf[(dl >> 5) * 64 + 32 + lane] += p1;
                if (lane < 3) buf[384 + (dl >> 5) * 4 + lane] += rb((lane == 0 ? df[0] : lane == 1 ? df[1] : df[2]) * rb(cs));
            }
        }
    }
    __syncwarp();
}

__global__ void __launch_bounds__(kThreads, 1)
egnn_kernel(const __nv_bfloat16* __restrict__ h, const __nv_bfloat16* __restrict__ pos,
            const __nv_bfloat16* __restrict__ e_attr, const int* __restrict__ src,
            const int* __restrict__ dst, const __nv_bfloat16* __restrict__ w_e,
            const __nv_bfloat16* __restrict__ w_x, const __nv_bfloat16* __restrict__ w_h,
            __nv_bfloat16* __restrict__ out_h, __nv_bfloat16* __restrict__ out_pos) {
    extern __shared__ __align__(128) unsigned char smem[];
    const uint32_t sb = (uint32_t)__cvta_generic_to_shared(smem);
    const int tid = threadIdx.x, lane = tid & 31;
    const int warp = __reduce_max_sync(~0u, tid >> 5);
    const int g = lane >> 2, t = lane & 3;
    const int cta = blockIdx.x;
    TSTAMP(0);

    const int e0 = cta * kChunk;
    const int ne4 = min(kChunk, kE - e0) >> 2;
    int4 dv[3], sv[3];
#pragma unroll
    for (int k = 0; k < 3; k++) dv[k] = ldg_stream((const int4*)(dst + e0) + min(tid + k * kThreads, ne4 - 1));
    unsigned epoch;
    asm volatile("ld.relaxed.gpu.global.u32 %0, [%1];" : "=r"(epoch) : "l"(g_epoch + cta) : "memory");
#pragma unroll
    for (int k = 0; k < 3; k++) sv[k] = ldg_stream((const int4*)(src + e0) + min(tid + k * kThreads, ne4 - 1));
    const int nbase = cta * kNPC;
    const int ncta = min(kNPC, kN - nbase);
    uint32_t px = 0, py = 0, pz = 0;
    {
        const int dloc = warp + 16 * (lane >> 3) + 32 * (lane & 7);
        if (lane < 16 && (lane & 7) < 6 && dloc < ncta) {
            const unsigned short* p = (const unsigned short*)pos + (size_t)(nbase + dloc) * 3;
            px = ldg16(p); py = ldg16(p + 1); pz = ldg16(p + 2);
        }
    }
#pragma unroll
    for (int k = 0; k < 9; k++) {
        const int i = tid + k * kThreads;
        if (i < kG * 32) sts128(sb + SM_REC + i * 16, 0u, 0u, 0u, 0u);
    }
    if (tid < 144 + 32 + 8 + 16) sts32(sb + SM_HIST + tid * 4, 0u);
    else if (tid >= 256 && tid < 384) {
        const int w = tid - 256, r = (w >> 2) & 7, j = w < 64 ? r + 6 * (w >> 5) : r;
        sts32(sb + SM_OH + w * 4, (r < 6 && (j >> 1) == (w & 3)) ? 0x3C00u << ((j & 1) * 16) : 0u);
    }
    __syncthreads();
#pragma unroll
    for (int q = 0; q < 3; q++) {
        const int i = tid + q * kThreads, r = i >> 3, c = i & 7;
        if (i < 145 * 8) cp16(sb + SM_WE + r * 128 + ((c ^ (r & 7)) << 4), (const uint4*)w_e + i);
    }
    if (tid >= kThreads - 8) cp16(sb + SM_WX + (tid & 7) * 16, (const uint4*)w_x + (tid & 7));
#pragma unroll
    for (int q = 0; q < 3; q++) {
        const int i = tid + q * kThreads, r = i >> 3, c = i & 7;
        const bool ok = r < ncta;
        cp16z(sb + SM_H + r * 128 + ((c ^ (r & 7)) << 4), (const uint4*)h + (ok ? (size_t)nbase * 8 + i : 0), ok ? 0u : ~0u);
    }
    cp_commit();
    epoch += (epoch & 0xFFFFFFu) == 0xFFFFFFu ? 2 : 1;
    const uint32_t tag = epoch << 8;
    TDEP(11, dv[0].x);

#pragma unroll
    for (int k = 0; k < 3; k++) {
        const int i = tid + k * kThreads;
        const int d4[4] = {dv[k].x, dv[k].y, dv[k].z, dv[k].w};
        const int s4[4] = {sv[k].x, sv[k].y, sv[k].z, sv[k].w};
        if (k < 2 || i < ne4) {
            uint32_t bin[4], rank[4];
#pragma unroll
            for (int q = 0; q < 4; q++) {
                bin[q] = __umulhi((uint32_t)d4[q], kBinMul);
                rank[q] = atoms_inc(sb + SM_HIST + bin[q] * 4);
            }
#pragma unroll
            for (int q = 0; q < 4; q++) {
                const uint32_t w0 = (uint32_t)s4[q] + ((uint32_t)(i * 4 + q) << 15);
                const uint32_t w1 = (uint32_t)d4[q] + tag - bin[q] * kNPC;
                if (rank[q] < 64) sts64(sb + SM_REC + bin[q] * 512 + ((rank[q] ^ ((2 * bin[q]) & 14)) << 3), w0, w1);
            }
            if ((rank[0] | rank[1] | rank[2] | rank[3]) >= 64) {
#pragma unroll
                for (int q = 0; q < 4; q++) {
                    if (rank[q] >= 64) {
                        const uint32_t w1 = (uint32_t)d4[q] + tag - bin[q] * kNPC;
                        st_relaxed(g_ovf + cta * kChunk + atoms_inc(sb + SM_MISC + 8), (uint32_t)s4[q] + ((uint32_t)(i * 4 + q) << 15), w1, bin[q], w1);
                    }
                }
            }
        }
    }
    if (lane < 16) {
        const int j = 6 * (lane >> 3) + (lane & 7);
        const bool v = (lane & 7) < 6;
        sts128(sb + SM_POS + warp * kPosStride + lane * 16, (px << 16) | (v && j == 8 ? 0x3F80u : 0u), (py << 16) | (v && j == 9 ? 0x3F80u : 0u),
               (pz << 16) | (v && j == 10 ? 0x3F80u : 0u), v && j == 11 ? 0x3F80u : 0u);
    } else {
        const uint32_t o = 0x3C00u << ((lane & 1) * 16), r = (lane & 7) >> 1;
        sts128(sb + SM_POS + warp * kPosStride + lane * 16, r == 0 ? o : 0u, r == 1 ? o : 0u, r == 2 ? o : 0u, 0u);
    }
    TSTAMP(1);
    __syncthreads();
    TDEP(14, lds32(sb + SM_HIST));
    uint4 tw[6];
    const unsigned* hdrp = g_hdr + min(lane * kCol + warp, kG - 1) * 160 + cta;
    uint32_t hdr;
    {
        const uint32_t novf = lds32(sb + SM_MISC + 8);
        if (tid < 136) asm volatile("st.relaxed.gpu.global.u32 [%0], %1;" :: "l"(g_hdr + cta * 160 + tid), "r"(lds32(sb + SM_HIST + tid * 4) | (novf << 13) | (epoch << 26)) : "memory");
        if (tid == 160 && (novf & 1)) st_relaxed(g_ovf + cta * kChunk + novf, 0u, 0u, 0u, 0u);
        const uint32_t lim = ((lane ^ (warp & 7)) >> 1) * 4;
#pragma unroll
        for (int s = 0; s < 9; s++) {
            if (lim < lds32(sb + SM_HIST + (s * kWarps + warp) * 4)) {
                const uint4 v = lds128(sb + SM_REC + s * (kWarps * 512) + tid * 16);
                st_relaxed(g_rec + cta * (kG * 32) + s * kThreads + tid, v.x, v.y, v.z, v.w);
            }
        }
        cp_wait<0>();
        TSTAMP(12);
        __syncthreads();
        uint32_t mx = project(sb, warp, lane, [&](int step) { if (step == 11) hdr = ld_relaxed32(hdrp); }, tw);
        if (warp < 8) {
            put_table(tw, warp, lane, nbase, ncta);
            mx = __reduce_max_sync(~0u, mx);
            if (lane == 0) asm volatile("red.shared.max.u32 [%0], %1;" :: "r"(sb + SM_MISC), "r"(mx) : "memory");
        }
    }
    TSTAMP(13);
#pragma unroll
    for (int q = 0; q < 2; q++) {
        const int i = tid + q * kThreads, r = i >> 3, c = i & 7;
        cp16(sb + SM_WH + r * 128 + ((c ^ (r & 7)) << 4), (const uint4*)w_h + (q ? 64 + feat(r - 64) : r) * 8 + c);
    }
    cp_commit();
    __syncthreads();
    TSTAMP(3);

    auto place = [&](uint32_t w0, uint32_t x, uint32_t ebase, uint32_t rank) {
        asm volatile("{.reg .pred p; setp.lt.u32 p, %3, %4; @p st.shared.u32 [%0], %1; @p st.shared.u32 [%0+%5], %2;}"
                     :: "r"(sb + SM_LS + (x & 31) * (kCapW * 4) + rank * 4), "r"(w0 & 0x7FFFu),
                        "r"(((w0 >> 15) + ebase) | ((x << 23) & 0x70000000u)), "r"(rank), "n"(kCapW), "n"(kLQ) : "memory");
    };
    unsigned spin = 0;
    if (warp == kWarps - 1) {
        if (lane == 0) {
            asm volatile("fence.acq_rel.gpu;" ::: "memory");
            asm volatile("st.relaxed.gpu.global.u16 [%0], %1;" :: "l"((unsigned short*)g_flag0 + cta), "h"((unsigned short)(tag | (lds32(sb + SM_MISC) >> 23))) : "memory");
        }
        __syncwarp();
        TSTAMP(2);
#pragma unroll
        for (int r = 0; r < 17; r++) {
            const uint32_t w = lds32(sb + SM_WE + (128 + r) * 128 + (((feat(2 * lane) >> 1) ^ ((r & 7) << 2)) << 2));
            sts32(sb + SM_W3 + r * 128 + ((lane ^ ((r & 7) << 2)) << 2), bf2h(hmul2(w, 0x3F003F00u)));
        }
        __nanosleep(600);
        const uint32_t tag2 = (tag & 0xFF00u) * 0x10001u;
        uint4 v;
        do {
            asm volatile("ld.acquire.gpu.global.v4.u32 {%0,%1,%2,%3}, [%4];" : "=r"(v.x), "=r"(v.y), "=r"(v.z), "=r"(v.w) : "l"(g_flag0 + min(lane, 16)) : "memory");
            if (lane >= 16) v.z = v.w = v.x;
            v.x ^= tag2; v.y ^= tag2; v.z ^= tag2; v.w ^= tag2;
            if (++spin > kSpinLimit) __trap();
        } while ((v.x | v.y | v.z | v.w) & 0xFF00FF00u);
        uint32_t mx = __vmaxu2(__vmaxu2(v.x, v.y), __vmaxu2(v.z, v.w));
        mx = max(mx & 255, mx >> 16);
        mx = __reduce_max_sync(~0u, mx);
        if (lane == 0) sts32(sb + SM_MISC + 4, mx);
        TSTAMP(4);
    } else {
        const uint4* recp = g_rec + (warp * kG + cta) * 32 + (lane ^ (cta & 7));
        while ((hdr ^ (epoch << 26)) >> 26) {
            hdr = ld_relaxed32(hdrp);
            if (++spin > kSpinLimit) __trap();
        }
        hdr = lane * kCol + warp < kG ? hdr & 0x3FFFFFFu : 0u;
        uint4 rv[kSegPerWarp];
        uint32_t cnt[kSegPerWarp];
#pragma unroll
        for (int s = 0; s < kSegPerWarp; s++) {
            cnt[s] = __shfl_sync(~0u, hdr, s) & 0x1FFF;
            rv[s] = make_uint4(0, tag, 0, tag);
            if (2 * lane < cnt[s]) rv[s] = ld_relaxed(recp + s * (kCol * kG * 32));
        }
        if (lane < kSegPerWarp) sts32(sb + SM_SEG + (lane * kCol + warp) * 4, hdr);
        uint32_t ovb = __ballot_sync(~0u, (hdr & 0x1FFF) > 64);
        uint4 ov = make_uint4(0, 0, 0, 0), ov2 = ov;
        if (ovb) {
            const int s1 = __ffs(ovb) - 1, s2 = __ffs(ovb & (ovb - 1)) - 1;
            if (lane < (__shfl_sync(~0u, hdr, s1) >> 13)) ov = ld_relaxed(g_ovf + (s1 * kCol + warp) * kChunk + lane);
            if (lane < (__shfl_sync(~0u, hdr, s2) >> 13)) ov2 = ld_relaxed(g_ovf + (s2 * kCol + warp) * kChunk + lane);
        }
        uint32_t rk[kSegPerWarp][2];
#pragma unroll
        for (int s = 0; s < kSegPerWarp + PD; s++) {
            if (s < kSegPerWarp) {
                while (__any_sync(~0u, (rv[s].y ^ tag) >= 256 || ((rv[s].w ^ tag) >= 256 && 2 * lane + 1 < cnt[s]))) {
                    if (2 * lane < cnt[s]) rv[s] = ld_relaxed(recp + s * (kCol * kG * 32));
                    if (++spin > kSpinLimit) __trap();
                }
                if (s == 0) TSTAMP(9);
                rk[s][0] = atoms_inc_lt(sb + SM_WCNT + (rv[s].y & 31) * 4, 2 * lane, cnt[s]);
                rk[s][1] = atoms_inc_lt(sb + SM_WCNT + (rv[s].w & 31) * 4, 2 * lane + 1, cnt[s]);
            }
            if (s >= PD) {
                place(rv[s - PD].x, rv[s - PD].y, ((s - PD) * kCol + warp) * kChunk, rk[s - PD][0]);
                place(rv[s - PD].z, rv[s - PD].w, ((s - PD) * kCol + warp) * kChunk, rk[s - PD][1]);
            }
        }
        TSTAMP(5);
        for (; ovb; ovb &= ovb - 1) {
            const uint32_t sg = __shfl_sync(~0u, hdr, __ffs(ovb) - 1), b = (__ffs(ovb) - 1) * kCol + warp;
            for (uint32_t i = lane; i < (sg >> 13); i += 32) {
                while (((ov.y ^ tag) | (ov.w ^ tag)) >= 256) {
                    ov = ld_relaxed(g_ovf + b * kChunk + i);
                    if (++spin > kSpinLimit) __trap();
                }
                if (ov.z == cta) place(ov.x, ov.y, b * kChunk, atoms_inc(sb + SM_WCNT + (ov.y & 31) * 4));
                ov.y = 0;
            }
            ov = ov2;
            ov2.y = 0;
        }
        TSTAMP(10);
    }
    uint32_t aw[4][4], w3[4][4];
    uint32_t wx[4];
#pragma unroll
    for (int j = 0; j < 4; j++) wx[j] = bf2h(lds16(sb + SM_WX + feat(16 * j + g) * 2) | (lds16(sb + SM_WX + feat(16 * j + 8 + g) * 2) << 16));
    cp_wait<0>();
    __syncthreads();
    TSTAMP(6);

    if (tid == 0) g_epoch[cta] = epoch;

    int w2;
    {
        const uint32_t key = (lds32(sb + SM_WCNT + lane * 4) << 5) | lane;
        const int r1 = __popc(__ballot_sync(~0u, key < __shfl_sync(~0u, key, warp)) & 0xFFFFu);
        const uint32_t key2 = __shfl_sync(~0u, key, lane | 16);
        int r2 = 0;
#pragma unroll
        for (int j = 0; j < 8; j++) r2 += __shfl_sync(~0u, key, 16 + ((lane >> 4) << 3) + j) > key2;
        r2 += __shfl_xor_sync(~0u, r2, 16);
        w2 = __ffs(__ballot_sync(~0u, r2 == r1)) - 1;
        const int k = lane & 7, j = lane < 16 ? k : 8 + (k >> 1);
        const int r = j < 6 ? warp + 32 * j : w2 + 16 + 32 * (j - 6), u = (lane >> 3) & 1, r3 = 1 + k + ((lane >> 4) << 3);
        const uint32_t a = lane >= 16 && (k & 1) ? sb + SM_W3 + (u << 4) : sb + SM_A + r * 128 + ((u ^ ((r + (r >> 5)) & 7)) << 4);
#pragma unroll
        for (int i = 0; i < 4; i++) {
            ldsm4t(aw[i], a ^ (i << 5));
            ldsm4t(w3[i], (sb + SM_W3 + r3 * 128 + ((u ^ (r3 & 7)) << 4)) ^ (i << 5));
        }
    }
    const uint32_t lsb = sb + SM_LS + warp * (kCapW * 4);
    const uint32_t stb = sb + SM_STAGE + warp * kStageBytes;
    const int lx = lane ^ ((lane >> 1) & 4) ^ (lane >> 4);
    const uint32_t cpB_ = stb + (lx << 4);
    const uint32_t ldB_ = stb + g * 128 + ((t ^ ((g & 1) << 2) ^ (g >> 1)) << 4);
    const uint32_t ldT_ = stb + ((lane & 7) + ((lane >> 4) << 3)) * 128 + ((((lane >> 3) & 1) ^ ((lane & 1) << 2) ^ ((lane >> 1) & 3)) << 4);
    const uint32_t ldE_ = stb + 2048 + ((lane & 7) + ((lane >> 4) << 3)) * 32 + ((((lane >> 3) ^ (lane >> 2)) & 1) << 4);
    uint32_t ohb = (lane & 8) ? sb + SM_POS + warp * kPosStride : sb + SM_OH;
    const uint32_t tabo = (lane & 7) << 4, eao = ((lx ^ (lane >> 3)) & 1) << 4;
    uint64_t tabp = (uint64_t)__cvta_generic_to_global(g_tab) + tabo;
    uint64_t eap = (uint64_t)__cvta_generic_to_global(e_attr) + eao;
    sts128(stb + 1024 + lane * 16, (uint32_t)tabp, (uint32_t)(tabp >> 32), (uint32_t)eap, (uint32_t)(eap >> 32));
    asm volatile("ld.volatile.shared.v2.u64 {%0,%1}, [%2];" : "=l"(tabp), "=l"(eap) : "r"(stb + 1024 + lane * 16) : "memory");
    sts128(stb + 512 + lane * 16, wx[0], wx[1], wx[2], wx[3]);
    { const uint4 w = lds128v(stb + 512 + lane * 16); wx[0] = w.x; wx[1] = w.y; wx[2] = w.z; wx[3] = w.w; }
    sts128(stb + lane * 16, cpB_, cpB_ ^ 32, ldB_, ldE_);
    sts128(stb + 1536 + lane * 16, ldT_, ldT_ ^ 32, ldT_ ^ 64, ldT_ ^ 96);
    const uint4 ad = lds128v(stb + lane * 16), at = lds128v(stb + 1536 + lane * 16);
    const uint32_t cpB = ad.x, cpB2 = ad.y, ldB = ad.z, ldE = ad.w, ldT[4] = {at.x, at.y, at.z, at.w};
    float acc[4][4], accp[4];
#pragma unroll
    for (int i = 0; i < 4; i++) { acc[i][0] = acc[i][1] = acc[i][2] = acc[i][3] = 0.f; accp[i] = 0.f; }
    auto switch_window = [&]() {
        __syncwarp();
        const int lane = fresh_lane();
        sts128(lsb + lane * 16, pack_bf16(acc[0][0], acc[0][1]), pack_bf16(acc[0][2], acc[0][3]), pack_bf16(acc[1][0], acc[1][1]), pack_bf16(acc[1][2], acc[1][3]));
        sts128(lsb + 512 + lane * 16, pack_bf16(acc[2][0], acc[2][1]), pack_bf16(acc[2][2], acc[2][3]), pack_bf16(acc[3][0], acc[3][1]), pack_bf16(acc[3][2], acc[3][3]));
        sts32(lsb + kLQ + lane * 4, pack_bf16(128.f * accp[0], 128.f * accp[1]));
#pragma unroll
        for (int i = 0; i < 4; i++) { acc[i][0] = acc[i][1] = acc[i][2] = acc[i][3] = 0.f; accp[i] = 0.f; }
#pragma unroll
        for (int j = 0; j < 3; j++) {
            const int r = j * 4 + (lane >> 3), hi = r < 6 ? r : r - 6, c = lane & 7, dloc = (r < 6 ? warp : 16 + w2) + 32 * hi;
            const bool ok = dloc < ncta;
            cp16z((r < 6 ? lsb + kLQ + 128 : sb + SM_H2 + warp * 768) + hi * 128 + ((c ^ hi) << 4), (const uint4*)h + (size_t)(ok ? nbase + dloc : 0) * 8 + c, ok ? 0u : ~0u);
        }
        ohb = ((lane & 8) ? sb + SM_POS + w2 * kPosStride : sb + SM_OH) + 128;
    };
    uint32_t pS, pQ, pD, qd;
    auto issue = [&](int lo, int st, bool on) {
        const uint4 s4 = lds128(pS + lo);
        const uint32_t q = lds32(pQ + lo);
        cp16g<128>(cpB + st, tabp, s4.x, on);
        cp16g<128>(cpB2 + st + 512, tabp, s4.y, on);
        cp16g<128>(cpB + st + 1024, tabp, s4.z, on);
        cp16g<128>(cpB2 + st + 1536, tabp, s4.w, on);
        cp16g<32>(cpB + st + 2048, eap, q & 0xFFFFFFu, on);
        cp_commit();
    };
    auto tile = [&](int sc, int lo, bool on) {
        const uint32_t oa = ohb + (qd >> 24);
        uint32_t oh[4], s0, s1;
        ldsm4(oh, oa);
        ldsm2t(s0, s1, oa + 256);
        cp_wait<2>();
        __syncwarp();
        uint32_t ef[4], pa, pb;
        const uint4 x0 = lds128(ldB + sc), x1 = lds128(ldB + sc + 1024);
        ldsm4(ef, ldE + sc);
        uint32_t c[4][4];
#pragma unroll
        for (int i = 0; i < 4; i++) ldsm4t(c[i], ldT[i] + sc);
#pragma unroll
        for (int i = 0; i < 4; i++) ef[i] = bf2h(ef[i]);
        const uint32_t d0 = hsub2(oh[3], __byte_perm(bitsel<0x003F003Fu>(bitsel<0x00070007u>(x0.x, x0.y << 3), x0.z << 6), 0, 0x2044));
        const uint32_t d1 = hsub2(oh[1], __byte_perm(bitsel<0x003F003Fu>(bitsel<0x00070007u>(x1.x, x1.y << 3), x1.z << 6), 0, 0x2044));
        const uint32_t q0 = bf2h(hmul2(d0, d0)), q1 = bf2h(hmul2(d1, d1));
        auto pre = [&](int i) {
            mma_h(c[i][0], c[i][1], w3[i], ef[0], ef[1]);
            mma_h(c[i][2], c[i][3], w3[i], ef[2], ef[3]);
            mma_h(c[i][0], c[i][1], aw[i], oh[0], q0);
            mma_h(c[i][2], c[i][3], aw[i], oh[2], q1);
        };
        auto act = [&](int i) {
#pragma unroll
            for (int q = 0; q < 4; q++) c[i][q] = silu_half2(c[i][q]);
            mma_f16(acc[i], c[i], s0, s1);
            pa = hfma2_hi(c[i][1], wx[i], hfma2_lo(c[i][0], wx[i], i ? pa : 0u));
            pb = hfma2_hi(c[i][3], wx[i], hfma2_lo(c[i][2], wx[i], i ? pb : 0u));
        };
        pre(0);
        pre(1);
        act(0);
        pre(2);
        act(1);
        pre(3);
        act(2);
        __syncwarp();
        qd = lds32(pD + lo + 64);
        issue(lo + 192, sc, on);
        act(3);
        float cs[4];
        mma_f16_k8_init(cs, movm(pa), movm(pb), 0x3C003C00u);
        const uint32_t cp = pack_bf16(cs[0], cs[2]);
        const uint32_t v0 = hmul2_lo(d0, cp), v1 = hmul2_hi(d1, cp);
        mma_bf16(accp, movm(v0), v0, movm(v1), v1, s0, s1);
    };
    bool synced = false;
    for (;;) {
        int sched, delta = 0;
        uint32_t first;
        __syncwarp();
        const int lane = fresh_lane();
        const uint32_t lsb2 = sb + SM_LS + (16 + w2) * (kCapW * 4);
        const uint32_t cnt0 = __reduce_max_sync(~0u, lds32(sb + SM_WCNT + warp * 4)), cnt1 = __reduce_max_sync(~0u, lds32(sb + SM_WCNT + 64 + w2 * 4));
        if (cnt0 <= kCapW && cnt1 <= kCapW) {
            const int n0 = (cnt0 + 15) >> 4, n1 = (cnt1 + 15) >> 4;
            const int i = (lane < 16 ? cnt0 : cnt1) + (lane & 15);
            const uint32_t a = (lane < 16 ? lsb : lsb2) + i * 4;
            if (i < 16 * (lane < 16 ? n0 : n1)) { sts32(a, nbase); sts32(a + kLQ, kPadQ | e0); }
            first = lsb; sched = n0 | ((n0 + n1) << 8); delta = lsb2 - lsb - 64 * n0;
            sched |= 1 << 29;
        } else {
            const uint32_t cur = __reduce_max_sync(~0u, lds32(sb + SM_CUR + warp * 4));
            int n = 0, cur_win = cur >> 24, cur_seg = (cur >> 16) & 255, cur_pos = cur & 0xFFFF;
            while (cur_seg < kG && n <= kCapW - 48) {
                const uint32_t sg = __reduce_max_sync(~0u, lds32(sb + SM_SEG + cur_seg * 4));
                const int len = 64 + ((sg & 0x1FFF) > 64 ? sg >> 13 : 0), i = cur_pos + lane;
                uint2 v = make_uint2(0, 255);
                if (i < 64) { if (i < (int)(sg & 0x1FFF)) v = __ldcg((const uint2*)g_rec + (cur_seg * kG + cta) * 64 + (i ^ ((2 * cta) & 14))); }
                else if (i < len) {
                    const uint4 o = __ldcg(g_ovf + cur_seg * kChunk + i - 64);
                    if (o.z == cta) v = make_uint2(o.x, o.y);
                }
                const bool hit = (v.y & 255) != 255 && (int)(v.y & 31) == (cur_win ? 16 + w2 : warp);
                const uint32_t bal = __ballot_sync(~0u, hit);
                if (hit) {
                    const int k = n + __popc(bal & ((1u << lane) - 1));
                    sts32(lsb2 + k * 4, v.x & 0x7FFFu);
                    sts32(lsb2 + kLQ + k * 4, ((v.x >> 15) + cur_seg * kChunk) | ((v.y << 23) & 0x70000000u));
                }
                n += __popc(bal);
                cur_pos += 32;
                if (cur_pos >= len) { cur_pos = 0; cur_seg++; }
            }
            if (lane < 16) { sts32(lsb2 + (n + lane) * 4, nbase); sts32(lsb2 + kLQ + (n + lane) * 4, kPadQ | e0); }
            const int nt = (n + 15) >> 4;
            first = lsb2; sched = 255 | (nt << 8);
            uint32_t nxt = (cur_win << 24) | (cur_seg << 16) | cur_pos;
            if (cur_seg == kG) {
                if (cur_win == 0) { sched = nt | (nt << 8); nxt = 1u << 24; } else sched |= 1 << 29;
            }
            __syncwarp();
            if (lane == 0) sts32(sb + SM_CUR + warp * 4, nxt);
        }
        __syncwarp();
        pS = first + (lane >> 3) * 16;
        const int pe = (lane ^ ((lane >> 1) & 4)) >> 1, pd = (lane ^ ((lane >> 1) & 8)) & 15;
        pQ = first + kLQ + (4 * (pe & 3) + (pe >> 2)) * 4;
        pD = first + kLQ + (4 * (pd & 3) + (pd >> 2)) * 4;
        sched = __reduce_max_sync(~0u, sched);
        const int n0 = (int8_t)sched * 64, nt = ((sched >> 8) & 255) * 64, ntm = __reduce_max_sync(~0u, nt - 192);
        if (n0 == 0) { pS += delta; pQ += delta; pD += delta; }
        issue(0, 0, nt > 0);
        qd = lds32(pD);
        if (n0 == 64) { pS += delta; pQ += delta; }
        issue(64, kStageStride, nt > 64);
        if (!synced) { __syncthreads(); synced = true; }
        if (n0 == 128) { pS += delta; pQ += delta; }
        issue(128, 2 * kStageStride, nt > 128);
        int sc = 0, ev = 0;
#pragma unroll 1
        for (int lo = 0;; lo += 64) {
            if (__builtin_expect(lo == ev, 0)) {
                if (lo == n0 - 192) { pS += delta; pQ += delta; }
                if (lo == n0 - 64) pD += delta;
                if (lo == n0) switch_window();
                if (lo == nt) break;
                ev = lo < n0 - 192 ? n0 - 192 : lo < n0 ? lo + 64 : nt;
            }
            tile(sc, lo, lo < ntm);
            sc = sc == 2 * kStageStride ? 0 : sc + kStageStride;
        }
        if (sched & (1 << 29)) break;
    }
    TSTAMP(7);

    {
        const int lane = fresh_lane(), g = lane >> 2, t = lane & 3;
        uint4 ma = lds128(lsb + lane * 16), mb = lds128(lsb + 512 + lane * 16);
        {
            uint32_t z = hadd2(hadd2(hadd2(ma.x, ma.y), hadd2(ma.z, ma.w)), hadd2(hadd2(mb.x, mb.y), hadd2(mb.z, mb.w)));
            z = hadd2(z, lds32(lsb + kLQ + lane * 4));
            float f = accp[0] + accp[1];
#pragma unroll
            for (int i = 0; i < 4; i++) f += (acc[i][0] + acc[i][1]) + (acc[i][2] + acc[i][3]);
            f += __uint_as_float(z << 16) + __uint_as_float(z & 0xFFFF0000u);
            if (__any_sync(~0u, !(fabsf(f) < __int_as_float(0x7F800000)) || lds32(sb + SM_MISC + 4) >= 127 + 15)) {
                float* buf = (float*)(smem + SM_STAGE + kStageStride + warp * kStageBytes);
#pragma unroll 1
                for (int sub = 0; sub < 2; sub++) {
                    exact_window(h, pos, e_attr, w_e, w_x, (const uint32_t*)(smem + SM_SEG), buf, sub ? 16 + w2 : warp);
#pragma unroll
                    for (int i = 0; i < 4; i++)
#pragma unroll
                        for (int q = 0; q < 4; q++) acc[i][q] = t < 3 ? buf[(2 * t + (q & 1)) * 64 + feat(16 * i + 8 * (q >> 1) + g)] : 0.f;
                    accp[0] = t < 3 ? buf[384 + 8 * t + (g >> 1)] * (1.f / 128.f) : 0.f;
                    accp[1] = t < 3 ? buf[388 + 8 * t + (g >> 1)] * (1.f / 128.f) : 0.f;
                    if (sub == 0) switch_window();
                    __syncwarp();
                }
                ma = lds128(lsb + lane * 16); mb = lds128(lsb + 512 + lane * 16);
            }
        }
        const uint32_t m0[4][2] = {{ma.x, ma.y}, {ma.z, ma.w}, {mb.x, mb.y}, {mb.z, mb.w}};
        float c[8][4];
#pragma unroll
        for (int j = 0; j < 8; j++) { c[j][0] = c[j][1] = c[j][2] = c[j][3] = 0.f; }
        uint32_t hf[4][4];
#pragma unroll
        for (int kk = 0; kk < 8; kk++) {
            const int ks = kk ^ 4;
            uint32_t a[4];
            if (ks < 4) {
                if (ks == 0) { cp_commit(); cp_wait<0>(); __syncwarp(); }
                const int hi = min(lane & 7, 5);
                ldsm4(hf[ks], ((lane & 8) ? sb + SM_H2 + warp * 768 : lsb + kLQ + 128) + hi * 128 + (((2 * ks + (lane >> 4)) ^ hi) << 4));
                a[0] = hf[ks][0]; a[1] = hf[ks][1]; a[2] = hf[ks][2]; a[3] = hf[ks][3];
            } else {
                const int i = ks - 4;
                a[0] = movm(m0[i][0]);
                a[1] = movm(pack_bf16(acc[i][0], acc[i][1]));
                a[2] = movm(m0[i][1]);
                a[3] = movm(pack_bf16(acc[i][2], acc[i][3]));
            }
#pragma unroll
            for (int i = 0; i < 4; i++) {
                uint32_t w[4];
                const int k = 16 * ks + (lane & 7) + ((lane >> 4) << 3);
                ldsm4t(w, sb + SM_WH + k * 128 + (((2 * i + ((lane >> 3) & 1)) ^ (k & 7)) << 4));
                mma_bf16(c[2 * i], a[0], a[1], a[2], a[3], w[0], w[2]);
                mma_bf16(c[2 * i + 1], a[0], a[1], a[2], a[3], w[1], w[3]);
            }
            if (kk == 3 && (g & 1) && g < 6 && t < 3) {
                const uint32_t dl[2] = {lds32(lsb + kLQ + lane * 4), pack_bf16(128.f * accp[0], 128.f * accp[1])};
#pragma unroll
                for (int sub = 0; sub < 2; sub++) {
                    const uint32_t pa = sb + SM_POS + (sub ? w2 : warp) * kPosStride + sub * 128 + t * 32 + (g >> 1) * 4;
                    const uint32_t o = hadd2(__byte_perm(lds32(pa), lds32(pa + 16), 0x7632), dl[sub]);
                    const int dloc = (sub ? 16 + w2 : warp) + 64 * t;
                    unsigned short* op = (unsigned short*)out_pos + (size_t)(nbase + dloc) * 3 + (g >> 1);
                    if (dloc < ncta) op[0] = (unsigned short)o;
                    if (dloc + 32 < ncta) op[96] = (unsigned short)(o >> 16);
                }
            }
        }
        __syncwarp();
#pragma unroll
        for (int ks = 0; ks < 4; ks++) {
            uint32_t o[4];
#pragma unroll
            for (int q = 0; q < 4; q++) {
                const float* cc = c[2 * ks + (q >> 1)] + 2 * (q & 1);
                o[q] = hadd2(hf[ks][q], pack_bf16(silu_half(0.5f * cc[0]), silu_half(0.5f * cc[1])));
            }
            const int r = lane & 15;
            stsm4(stb + r * 128 + (((2 * ks + (lane >> 4)) ^ (r & 7)) << 4), o[0], o[1], o[2], o[3]);
        }
        __syncwarp();
#pragma unroll
        for (int j = 0; j < 4; j++) {
            const int r = j * 4 + (lane >> 3), cc = lane & 7, dloc = (j < 2 ? warp : 16 + w2) + 32 * (r & 7);
            const uint4 v = lds128(stb + r * 128 + ((cc ^ (r & 7)) << 4));
            if (dloc < ncta) ((uint4*)out_h)[(size_t)(nbase + dloc) * 8 + cc] = v;
        }
    }
    TSTAMP(8);
}

}

extern "C" void kernel_launch(void* const* d_in, const int* in_sizes, int n_in, void* d_out, int out_size) {
    static bool init = false;
    if (!init) {
        cudaFuncSetAttribute(egnn_kernel, cudaFuncAttributeMaxDynamicSharedMemorySize, SM_TOTAL);
        init = true;
    }
    __nv_bfloat16* out = (__nv_bfloat16*)d_out;
    egnn_kernel<<<kG, kThreads, SM_TOTAL>>>(
        (const __nv_bfloat16*)d_in[0], (const __nv_bfloat16*)d_in[1], (const __nv_bfloat16*)d_in[2],
        (const int*)d_in[3], (const int*)d_in[4], (const __nv_bfloat16*)d_in[5],
        (const __nv_bfloat16*)d_in[6], (const __nv_bfloat16*)d_in[7], out, out + (size_t)kN * 64);
}
```

```cpp
#include <cuda_runtime.h>
#include <cuda_bf16.h>
#include <cuda_fp16.h>
#include <stdint.h>

namespace {

constexpr int kN = 25000;
constexpr int kE = 800000;
constexpr int kG = 132;
constexpr int kNPC = 190;
constexpr int kChunk = 6064;
constexpr int kThreads = 512;
constexpr int kWarps = 16;
constexpr int kCapW = 272;
constexpr int kStageBytes = 2560;
constexpr int kStageStride = kWarps * kStageBytes;
constexpr int kSegPerWarp = 9;
constexpr int kCol = kWarps - 1;
constexpr int kPosStride = 528;
constexpr uint32_t kBinMul = 22605092u;
constexpr unsigned kSpinLimit = 1u << 22;
constexpr uint32_t kPadQ = 6u << 28;

constexpr int SM_STAGE = 0;
constexpr int SM_REC = SM_STAGE;
constexpr int SM_WE = SM_STAGE + kG * 512;
constexpr int SM_H = SM_WE + 145 * 128;
constexpr int SM_A = SM_H + 192 * 128;
constexpr int SM_W3 = SM_A - 17 * 128;
constexpr int SM_H2 = SM_STAGE + 3 * kStageStride;
constexpr int SM_LS = SM_A + 192 * 128;
constexpr int kLQ = kWarps * 2 * kCapW * 4;
constexpr int SM_WH = SM_LS + 2 * kLQ;
constexpr int SM_POS = SM_WH + 16384;
constexpr int SM_OH = SM_POS + kWarps * kPosStride;
constexpr int SM_WX = SM_OH + 512;
constexpr int SM_HIST = SM_WX + 128;
constexpr int SM_WCNT = SM_HIST + 144 * 4;
constexpr int SM_MISC = SM_WCNT + 32 * 4;
constexpr int SM_CUR = SM_MISC + 32;
constexpr int SM_SEG = SM_CUR + 64;
constexpr int SM_TOTAL = SM_SEG + 144 * 4;
static_assert(SM_W3 >= 2 * kStageStride && SM_LS >= SM_H2 + kWarps * 768, "aliasing");
static_assert(SM_TOTAL <= 232448, "shared memory");

__device__ uint4 g_tab[kG * kNPC * 8];
__device__ uint4 g_rec[kG * kG * 32];
__device__ uint4 g_ovf[kG * kChunk];
__device__ uint4 g_flag0[17];
__device__ __align__(128) unsigned g_hdr[kG * 160];
__device__ unsigned g_epoch[kG];
#define TDEP(i, x)
#define TSTAMP(i)

__device__ __forceinline__ void mma_bf16(float (&c)[4], uint32_t a0, uint32_t a1, uint32_t a2, uint32_t a3, uint32_t b0, uint32_t b1) {
    asm volatile("mma.sync.aligned.m16n8k16.row.col.f32.bf16.bf16.f32 {%0,%1,%2,%3}, {%4,%5,%6,%7}, {%8,%9}, {%0,%1,%2,%3};"
        : "+f"(c[0]), "+f"(c[1]), "+f"(c[2]), "+f"(c[3]) : "r"(a0), "r"(a1), "r"(a2), "r"(a3), "r"(b0), "r"(b1));
}
__device__ __forceinline__ void mma_f16(float (&c)[4], const uint32_t (&a)[4], uint32_t b0, uint32_t b1) {
    asm volatile("mma.sync.aligned.m16n8k16.row.col.f32.f16.f16.f32 {%0,%1,%2,%3}, {%4,%5,%6,%7}, {%8,%9}, {%0,%1,%2,%3};"
        : "+f"(c[0]), "+f"(c[1]), "+f"(c[2]), "+f"(c[3]) : "r"(a[0]), "r"(a[1]), "r"(a[2]), "r"(a[3]), "r"(b0), "r"(b1));
}
__device__ __forceinline__ void mma_h(uint32_t& c0, uint32_t& c1, const uint32_t (&a)[4], uint32_t b0, uint32_t b1) {
    asm volatile("mma.sync.aligned.m16n8k16.row.col.f16.f16.f16.f16 {%0,%1}, {%2,%3,%4,%5}, {%6,%7}, {%0,%1};"
        : "+r"(c0), "+r"(c1) : "r"(a[0]), "r"(a[1]), "r"(a[2]), "r"(a[3]), "r"(b0), "r"(b1));
}
__device__ __forceinline__ void mma_f16_k8_init(float (&c)[4], uint32_t a0, uint32_t a1, uint32_t b0) {
    asm volatile("mma.sync.aligned.m16n8k8.row.col.f32.f16.f16.f32 {%0,%1,%2,%3}, {%4,%5}, {%6}, {%7,%7,%7,%7};"
        : "=f"(c[0]), "=f"(c[1]), "=f"(c[2]), "=f"(c[3]) : "r"(a0), "r"(a1), "r"(b0), "f"(0.f));
}
__device__ __forceinline__ uint32_t movm(uint32_t a) {
    uint32_t d; asm("movmatrix.sync.aligned.m8n8.trans.b16 %0, %1;" : "=r"(d) : "r"(a)); return d;
}
__device__ __forceinline__ void ldsm4(uint32_t (&r)[4], uint32_t a) {
    asm volatile("ldmatrix.sync.aligned.m8n8.x4.shared.b16 {%0,%1,%2,%3}, [%4];" : "=r"(r[0]), "=r"(r[1]), "=r"(r[2]), "=r"(r[3]) : "r"(a));
}
__device__ __forceinline__ void ldsm4t(uint32_t (&r)[4], uint32_t a) {
    asm volatile("ldmatrix.sync.aligned.m8n8.x4.trans.shared.b16 {%0,%1,%2,%3}, [%4];" : "=r"(r[0]), "=r"(r[1]), "=r"(r[2]), "=r"(r[3]) : "r"(a));
}
__device__ __forceinline__ void stsm4(uint32_t a, uint32_t r0, uint32_t r1, uint32_t r2, uint32_t r3) {
    asm volatile("stmatrix.sync.aligned.m8n8.x4.shared.b16 [%0], {%1,%2,%3,%4};" :: "r"(a), "r"(r0), "r"(r1), "r"(r2), "r"(r3) : "memory");
}
__device__ __forceinline__ uint4 lds128(uint32_t a) {
    uint4 v; asm volatile("ld.shared.v4.u32 {%0,%1,%2,%3}, [%4];" : "=r"(v.x), "=r"(v.y), "=r"(v.z), "=r"(v.w) : "r"(a)); return v;
}
__device__ __forceinline__ uint4 lds128v(uint32_t a) {
    uint4 v; asm volatile("ld.volatile.shared.v4.u32 {%0,%1,%2,%3}, [%4];" : "=r"(v.x), "=r"(v.y), "=r"(v.z), "=r"(v.w) : "r"(a) : "memory"); return v;
}
__device__ __forceinline__ uint32_t lds32(uint32_t a) {
    uint32_t v; asm volatile("ld.shared.u32 %0, [%1];" : "=r"(v) : "r"(a)); return v;
}
__device__ __forceinline__ uint32_t lds16(uint32_t a) {
    uint32_t v; asm volatile("ld.shared.u16 %0, [%1];" : "=r"(v) : "r"(a)); return v;
}
__device__ __forceinline__ void sts32(uint32_t a, uint32_t v) { asm volatile("st.shared.u32 [%0], %1;" :: "r"(a), "r"(v) : "memory"); }
__device__ __forceinline__ void sts64(uint32_t a, uint32_t x, uint32_t y) { asm volatile("st.shared.v2.u32 [%0], {%1,%2};" :: "r"(a), "r"(x), "r"(y) : "memory"); }
__device__ __forceinline__ uint32_t atoms_inc(uint32_t a) {
    uint32_t v; asm volatile("atom.shared.add.u32 %0, [%1], 1;" : "=r"(v) : "r"(a) : "memory"); return v;
}
__device__ __forceinline__ uint32_t atoms_inc_lt(uint32_t a, uint32_t i, uint32_t n) {
    uint32_t v; asm volatile("{.reg .pred p; setp.lt.u32 p, %2, %3; mov.b32 %0, -1; @p atom.shared.add.u32 %0, [%1], 1;}" : "=r"(v) : "r"(a), "r"(i), "r"(n) : "memory"); return v;
}
__device__ __forceinline__ void cp16(uint32_t d, const void* s) {
    asm volatile("cp.async.cg.shared.global [%0], [%1], 16;" :: "r"(d), "l"(s) : "memory");
}
__device__ __forceinline__ void cp16z(uint32_t d, const void* s, uint32_t flag) {
    asm volatile("{.reg .pred p; setp.lt.s32 p, %2, 0; cp.async.cg.shared.global [%0], [%1], 16, p;}" :: "r"(d), "l"(s), "r"(flag) : "memory");
}
__device__ __forceinline__ void cp_commit() { asm volatile("cp.async.commit_group;" ::: "memory"); }
template <int n> __device__ __forceinline__ void cp_wait() { asm volatile("cp.async.wait_group %0;" :: "n"(n) : "memory"); }
__device__ __forceinline__ int4 ldg_stream(const int4* p) {
    int4 v; asm volatile("ld.relaxed.gpu.global.v4.s32 {%0,%1,%2,%3}, [%4];" : "=r"(v.x), "=r"(v.y), "=r"(v.z), "=r"(v.w) : "l"(p) : "memory"); return v;
}
__device__ __forceinline__ uint32_t ldg16(const unsigned short* p) {
    uint32_t v; asm volatile("ld.relaxed.gpu.global.u16 %0, [%1];" : "=r"(v) : "l"(p) : "memory"); return v;
}
__device__ __forceinline__ uint32_t pack_bf16(float lo, float hi) {
    uint32_t d; asm("cvt.rn.bf16x2.f32 %0, %1, %2;" : "=r"(d) : "f"(hi), "f"(lo)); return d;
}
__device__ __forceinline__ uint32_t pack_f16(float lo, float hi) {
    uint32_t d; asm("cvt.rn.f16x2.f32 %0, %1, %2;" : "=r"(d) : "f"(hi), "f"(lo)); return d;
}
__device__ __forceinline__ uint32_t hmul2(uint32_t a, uint32_t b) { uint32_t d; asm("mul.rn.bf16x2 %0, %1, %2;" : "=r"(d) : "r"(a), "r"(b)); return d; }
__device__ __forceinline__ uint32_t hsub2(uint32_t a, uint32_t b) { uint32_t d; asm("sub.rn.bf16x2 %0, %1, %2;" : "=r"(d) : "r"(a), "r"(b)); return d; }
__device__ __forceinline__ uint32_t hadd2(uint32_t a, uint32_t b) { uint32_t d; asm("add.rn.bf16x2 %0, %1, %2;" : "=r"(d) : "r"(a), "r"(b)); return d; }
__device__ __forceinline__ float silu_half(float x) {
    float t; asm volatile("tanh.approx.f32 %0, %1;" : "=f"(t) : "f"(x)); return fmaf(x, t, x);
}
__device__ __forceinline__ uint32_t silu_half2(uint32_t x) {
    uint32_t d; asm volatile("{.reg .b32 t; tanh.approx.f16x2 t, %1; fma.rn.f16x2 %0, %1, t, %1;}" : "=r"(d) : "r"(x)); return d;
}
__device__ __forceinline__ uint32_t bf2h(uint32_t x) { return pack_f16(__uint_as_float(x << 16), __uint_as_float(x & 0xFFFF0000u)); }
__device__ __forceinline__ int feat(int p) { return (p & 33) | ((p & 6) << 2) | ((p >> 2) & 6); }
__device__ __forceinline__ void ldsm2t(uint32_t& r0, uint32_t& r1, uint32_t a) {
    asm volatile("ldmatrix.sync.aligned.m8n8.x2.trans.shared.b16 {%0,%1}, [%2];" : "=r"(r0), "=r"(r1) : "r"(a));
}
__device__ __forceinline__ void sts128(uint32_t a, uint32_t x, uint32_t y, uint32_t z, uint32_t w) {
    asm volatile("st.shared.v4.u32 [%0], {%1,%2,%3,%4};" :: "r"(a), "r"(x), "r"(y), "r"(z), "r"(w) : "memory");
}
template <int mul> __device__ __forceinline__ void cp16g(uint32_t d, uint64_t base, uint32_t idx, bool p) {
    asm volatile("{.reg .pred p; .reg .b64 a; setp.ne.u32 p, %3, 0; mul.wide.u32 a, %2, %4; add.s64 a, a, %1; @p cp.async.cg.shared.global [%0], [a], 16;}"
                 :: "r"(d), "l"(base), "r"(idx), "r"((uint32_t)p), "n"(mul) : "memory");
}
template <uint32_t m> __device__ __forceinline__ uint32_t bitsel(uint32_t a, uint32_t b) {
    uint32_t d; asm("lop3.b32 %0, %1, %2, %3, 0xE2;" : "=r"(d) : "r"(a), "n"(m), "r"(b)); return d;
}
__device__ __forceinline__ uint32_t hfma2_lo(uint32_t a, uint32_t b, uint32_t c) {
    uint32_t d; asm("{.reg .b16 l,h; .reg .b32 x; mov.b32 {l,h}, %2; mov.b32 x, {l,l}; fma.rn.f16x2 %0, %1, x, %3;}" : "=r"(d) : "r"(a), "r"(b), "r"(c)); return d;
}
__device__ __forceinline__ uint32_t hfma2_hi(uint32_t a, uint32_t b, uint32_t c) {
    uint32_t d; asm("{.reg .b16 l,h; .reg .b32 x; mov.b32 {l,h}, %2; mov.b32 x, {h,h}; fma.rn.f16x2 %0, %1, x, %3;}" : "=r"(d) : "r"(a), "r"(b), "r"(c)); return d;
}
__device__ __forceinline__ uint4 ld_relaxed(const uint4* p) {
    uint4 v; asm volatile("ld.relaxed.gpu.global.v4.u32 {%0,%1,%2,%3}, [%4];" : "=r"(v.x), "=r"(v.y), "=r"(v.z), "=r"(v.w) : "l"(p) : "memory"); return v;
}
__device__ __forceinline__ uint32_t ld_relaxed32(const unsigned* p) {
    uint32_t v; asm volatile("ld.relaxed.gpu.global.u32 %0, [%1];" : "=r"(v) : "l"(p) : "memory"); return v;
}
__device__ __forceinline__ void st_relaxed(uint4* p, uint32_t x, uint32_t y, uint32_t z, uint32_t w) {
    asm volatile("st.relaxed.gpu.global.v4.u32 [%0], {%1,%2,%3,%4};" :: "l"(p), "r"(x), "r"(y), "r"(z), "r"(w) : "memory");
}
__device__ __forceinline__ uint32_t hmul2_lo(uint32_t a, uint32_t b) {
    uint32_t d; asm("{.reg .b16 l,h; .reg .b32 x; mov.b32 {l,h}, %2; mov.b32 x, {l,l}; mul.rn.bf16x2 %0, %1, x;}" : "=r"(d) : "r"(a), "r"(b)); return d;
}
__device__ __forceinline__ uint32_t hmul2_hi(uint32_t a, uint32_t b) {
    uint32_t d; asm("{.reg .b16 l,h; .reg .b32 x; mov.b32 {l,h}, %2; mov.b32 x, {h,h}; mul.rn.bf16x2 %0, %1, x;}" : "=r"(d) : "r"(a), "r"(b)); return d;
}
template <int n> __device__ __forceinline__ uint32_t embed_bits(uint32_t w, uint32_t r) {
    constexpr uint32_t m = ((1u << n) - 1) * 0x10001u;
    r &= m;
    const uint32_t v = __vmaxu2((w & 0x7FFF7FFFu) + (0x10001u << (n - 1)), r) - r;
    return (v & ~m) | r | (w & 0x80008000u);
}

template <class F>
__device__ __forceinline__ uint32_t project(uint32_t sb, int warp, int lane, F hook, uint4 (&tw)[6]) {
    const int g = lane >> 2, t = lane & 3, row0 = (warp & 3) * 48, cg = warp >> 2;
    float c[3][4][4];
#pragma unroll
    for (int m = 0; m < 3; m++)
#pragma unroll
        for (int j = 0; j < 4; j++) { c[m][j][0] = c[m][j][1] = c[m][j][2] = c[m][j][3] = 0.f; }
    const uint32_t wa = sb + SM_WE + ((cg < 2 ? 64 : 0) + (lane & 7) + ((lane >> 4) << 3)) * 128 + (((4 * (cg & 1) + ((lane >> 3) & 1)) ^ (lane & 7)) << 4);
    const uint32_t ha = sb + SM_H + (row0 + (lane & 15)) * 128 + (((lane >> 4) ^ (lane & 7)) << 4);
#pragma unroll
    for (int ks = 0; ks < 4; ks++) {
        uint32_t w[2][4];
        ldsm4t(w[0], wa + ks * 2048);
        ldsm4t(w[1], (wa ^ 32) + ks * 2048);
#pragma unroll
        for (int m = 0; m < 3; m++) {
            uint32_t hf[4];
            ldsm4(hf, (ha ^ (ks << 5)) + m * 2048);
            hook(ks * 3 + m);
#pragma unroll
            for (int j = 0; j < 4; j++) mma_bf16(c[m][j], hf[0], hf[1], hf[2], hf[3], w[j >> 1][j & 1], w[j >> 1][2 + (j & 1)]);
        }
    }
    float mx = 0.f;
#pragma unroll
    for (int m = 0; m < 3; m++)
#pragma unroll
        for (int u = 0; u < 2; u++) {
            uint32_t wd[4];
#pragma unroll
            for (int j = 0; j < 4; j++) {
                mx = fmaxf(mx, fmaxf(fabsf(c[m][j][2 * u]), fabsf(c[m][j][2 * u + 1])));
                wd[j] = pack_f16(c[m][j][2 * u] * 0.5f, c[m][j][2 * u + 1] * 0.5f);
            }
            const int r = row0 + 16 * m;
            if (cg == 0) {
                const uint32_t p = __byte_perm(lds32(sb + SM_POS + (8 * u + g) * kPosStride + (r & 16) * 8 + (r >> 5) * 16 + 4 * t), 0, 0x4342);
                wd[0] = embed_bits<3>(wd[0], p);
                wd[1] = embed_bits<3>(wd[1], p >> 3);
                wd[2] = embed_bits<2>(wd[2], p >> 6);
            }
            tw[2 * m + u] = make_uint4(wd[0], wd[1], wd[2], wd[3]);
            if (cg >= 2) sts128(sb + SM_A + (r + 8 * u + g) * 128 + (((4 * (cg & 1) + t) ^ ((g + (r >> 5)) & 7)) << 4), wd[0], wd[1], wd[2], wd[3]);
        }
    return __float_as_uint(mx * 0.5f);
}

__device__ __forceinline__ void put_table(const uint4 (&tw)[6], int warp, int lane, int nbase, int ncta) {
    const int r = (warp & 3) * 48 + (lane >> 2);
#pragma unroll
    for (int i = 0; i < 6; i++)
        if (r + 8 * i < ncta) st_relaxed(g_tab + (size_t)(nbase + r + 8 * i) * 8 + (warp >> 2) * 4 + (lane & 3), tw[i].x, tw[i].y, tw[i].z, tw[i].w);
}
constexpr int kSendFirst = 4;
constexpr int PD = 2;
__device__ __forceinline__ int fresh_lane() { int l; asm volatile("mov.u32 %0, %%laneid;" : "=r"(l)); return l; }

__device__ __noinline__ void exact_window(const __nv_bfloat16* h, const __nv_bfloat16* pos, const __nv_bfloat16* e_attr,
                                          const __nv_bfloat16* w_e, const __nv_bfloat16* w_x, const uint32_t* seg, float* buf, int win) {
    const int lane = threadIdx.x & 31, cta = blockIdx.x;
    auto rb = [](float x) { return __bfloat162float(__float2bfloat16(x)); };
    for (int i = lane; i < 6 * 68; i += 32) buf[i] = 0.f;
    __syncwarp();
    for (int b = 0; b < kG; b++) {
        const int cnt = seg[b] & 0x1FFF, len = cnt > 64 ? 64 + (seg[b] >> 13) : cnt;
        for (int i0 = 0; i0 < len; i0 += 32) {
            const int i = i0 + lane;
            uint2 v = make_uint2(0, 255);
            if (i < 64) { if (i < cnt) v = __ldcg((const uint2*)g_rec + (b * kG + cta) * 64 + (i ^ ((2 * cta) & 14))); }
            else if (i < len) {
                const uint4 o = __ldcg(g_ovf + b * kChunk + i - 64);
                if (o.z == cta) v = make_uint2(o.x, o.y);
            }
            for (uint32_t bal = __ballot_sync(~0u, (v.y & 255) != 255 && (int)(v.y & 31) == win); bal; bal &= bal - 1) {
                const uint32_t w0 = __shfl_sync(~0u, v.x, __ffs(bal) - 1), dl = __shfl_sync(~0u, v.y, __ffs(bal) - 1) & 255;
                const int sn = w0 & 0x7FFF, dn = cta * kNPC + dl, e = (w0 >> 15) + b * kChunk;
                float df[3], d2 = 0.f, p0 = 0.f, p1 = 0.f;
                for (int c = 0; c < 3; c++) {
                    df[c] = rb(__bfloat162float(pos[dn * 3 + c]) - __bfloat162float(pos[sn * 3 + c]));
                    d2 += rb(df[c] * df[c]);
                }
                for (int k = 0; k < 145; k++) {
                    const float x = k == 128 ? rb(d2) : __bfloat162float(k < 64 ? h[dn * 64 + k] : k < 128 ? h[sn * 64 + k - 64] : e_attr[(size_t)e * 16 + k - 129]);
                    p0 = fmaf(x, __bfloat162float(w_e[k * 64 + lane]), p0);
                    p1 = fmaf(x, __bfloat162float(w_e[k * 64 + 32 + lane]), p1);
                }
                p0 = rb(silu_half(0.5f * rb(p0)));
                p1 = rb(silu_half(0.5f * rb(p1)));
                float cs = p0 * __bfloat162float(w_x[lane]) + p1 * __bfloat162float(w_x[32 + lane]);
                for (int o = 16; o; o >>= 1) cs += __shfl_xor_sync(~0u, cs, o);
                buf[(dl >> 5) * 64 + lane] += p0;
                buf[(dl >> 5) * 64 + 32 + lane] += p1;
                if (lane < 3) buf[384 + (dl >> 5) * 4 + lane] += rb((lane == 0 ? df[0] : lane == 1 ? df[1] : df[2]) * rb(cs));
            }
        }
    }
    __syncwarp();
}

__global__ void __launch_bounds__(kThreads, 1)
egnn_kernel(const __nv_bfloat16* __restrict__ h, const __nv_bfloat16* __restrict__ pos,
            const __nv_bfloat16* __restrict__ e_attr, const int* __restrict__ src,
            const int* __restrict__ dst, const __nv_bfloat16* __restrict__ w_e,
            const __nv_bfloat16* __restrict__ w_x, const __nv_bfloat16* __restrict__ w_h,
            __nv_bfloat16* __restrict__ out_h, __nv_bfloat16* __restrict__ out_pos) {
    extern __shared__ __align__(128) unsigned char smem[];
    const uint32_t sb = (uint32_t)__cvta_generic_to_shared(smem);
    const int tid = threadIdx.x, lane = tid & 31;
    const int warp = __reduce_max_sync(~0u, tid >> 5);
    const int g = lane >> 2, t = lane & 3;
    const int cta = blockIdx.x;
    TSTAMP(0);

    const int e0 = cta * kChunk;
    const int ne4 = min(kChunk, kE - e0) >> 2;
    int4 dv[3], sv[3];
#pragma unroll
    for (int k = 0; k < 3; k++) dv[k] = ldg_stream((const int4*)(dst + e0) + min(tid + k * kThreads, ne4 - 1));
    unsigned epoch;
    asm volatile("ld.relaxed.gpu.global.u32 %0, [%1];" : "=r"(epoch) : "l"(g_epoch + cta) : "memory");
#pragma unroll
    for (int k = 0; k < 3; k++) sv[k] = ldg_stream((const int4*)(src + e0) + min(tid + k * kThreads, ne4 - 1));
    const int nbase = cta * kNPC;
    const int ncta = min(kNPC, kN - nbase);
    uint32_t px = 0, py = 0, pz = 0;
    {
        const int dloc = warp + 16 * (lane >> 3) + 32 * (lane & 7);
        if (lane < 16 && (lane & 7) < 6 && dloc < ncta) {
            const unsigned short* p = (const unsigned short*)pos + (size_t)(nbase + dloc) * 3;
            px = ldg16(p); py = ldg16(p + 1); pz = ldg16(p + 2);
        }
    }
#pragma unroll
    for (int k = 0; k < 9; k++) {
        const int i = tid + k * kThreads;
        if (i < kG * 32) sts128(sb + SM_REC + i * 16, 0u, 0u, 0u, 0u);
    }
    if (tid < 144 + 32 + 8 + 16) sts32(sb + SM_HIST + tid * 4, 0u);
    else if (tid >= 256 && tid < 384) {
        const int w = tid - 256, r = (w >> 2) & 7, j = w < 64 ? r + 6 * (w >> 5) : r;
        sts32(sb + SM_OH + w * 4, (r < 6 && (j >> 1) == (w & 3)) ? 0x3C00u << ((j & 1) * 16) : 0u);
    }
    __syncthreads();
#pragma unroll
    for (int q = 0; q < 3; q++) {
        const int i = tid + q * kThreads, r = i >> 3, c = i & 7;
        if (i < 145 * 8) cp16(sb + SM_WE + r * 128 + ((c ^ (r & 7)) << 4), (const uint4*)w_e + i);
    }
    if (tid >= kThreads - 8) cp16(sb + SM_WX + (tid & 7) * 16, (const uint4*)w_x + (tid & 7));
#pragma unroll
    for (int q = 0; q < 3; q++) {
        const int i = tid + q * kThreads, r = i >> 3, c = i & 7;
        const bool ok = r < ncta;
        cp16z(sb + SM_H + r * 128 + ((c ^ (r & 7)) << 4), (const uint4*)h + (ok ? (size_t)nbase * 8 + i : 0), ok ? 0u : ~0u);
    }
    cp_commit();
    epoch += (epoch & 0xFFFFFFu) == 0xFFFFFFu ? 2 : 1;
    const uint32_t tag = epoch << 8;
    TDEP(11, dv[0].x);

#pragma unroll
    for (int k = 0; k < 3; k++) {
        const int i = tid + k * kThreads;
        const int d4[4] = {dv[k].x, dv[k].y, dv[k].z, dv[k].w};
        const int s4[4] = {sv[k].x, sv[k].y, sv[k].z, sv[k].w};
        if (k < 2 || i < ne4) {
            uint32_t bin[4], rank[4];
#pragma unroll
            for (int q = 0; q < 4; q++) {
                bin[q] = __umulhi((uint32_t)d4[q], kBinMul);
                rank[q] = atoms_inc(sb + SM_HIST + bin[q] * 4);
            }
#pragma unroll
            for (int q = 0; q < 4; q++) {
                const uint32_t w0 = (uint32_t)s4[q] + ((uint32_t)(i * 4 + q) << 15);
                const uint32_t w1 = (uint32_t)d4[q] + tag - bin[q] * kNPC;
                if (rank[q] < 64) sts64(sb + SM_REC + bin[q] * 512 + ((rank[q] ^ ((2 * bin[q]) & 14)) << 3), w0, w1);
            }
            if ((rank[0] | rank[1] | rank[2] | rank[3]) >= 64) {
#pragma unroll
                for (int q = 0; q < 4; q++) {
                    if (rank[q] >= 64) {
                        const uint32_t w1 = (uint32_t)d4[q] + tag - bin[q] * kNPC;
                        st_relaxed(g_ovf + cta * kChunk + atoms_inc(sb + SM_MISC + 8), (uint32_t)s4[q] + ((uint32_t)(i * 4 + q) << 15), w1, bin[q], w1);
                    }
                }
            }
        }
    }
    if (lane < 16) {
        const int j = 6 * (lane >> 3) + (lane & 7);
        const bool v = (lane & 7) < 6;
        sts128(sb + SM_POS + warp * kPosStride + lane * 16, (px << 16) | (v && j == 8 ? 0x3F80u : 0u), (py << 16) | (v && j == 9 ? 0x3F80u : 0u),
               (pz << 16) | (v && j == 10 ? 0x3F80u : 0u), v && j == 11 ? 0x3F80u : 0u);
    } else {
        const uint32_t o = 0x3C00u << ((lane & 1) * 16), r = (lane & 7) >> 1;
        sts128(sb + SM_POS + warp * kPosStride + lane * 16, r == 0 ? o : 0u, r == 1 ? o : 0u, r == 2 ? o : 0u, 0u);
    }
    TSTAMP(1);
    __syncthreads();
    TDEP(14, lds32(sb + SM_HIST));
    uint4 tw[6];
    const unsigned* hdrp = g_hdr + min(lane * kCol + warp, kG - 1) * 160 + cta;
    uint32_t hdr;
    {
        const uint32_t novf = lds32(sb + SM_MISC + 8);
        if (tid < 136) asm volatile("st.relaxed.gpu.global.u32 [%0], %1;" :: "l"(g_hdr + cta * 160 + tid), "r"(lds32(sb + SM_HIST + tid * 4) | (novf << 13) | (epoch << 26)) : "memory");
        if (tid == 160 && (novf & 1)) st_relaxed(g_ovf + cta * kChunk + novf, 0u, 0u, 0u, 0u);
        const uint32_t lim = ((lane ^ (warp & 7)) >> 1) * 4;
        auto send = [&](int s) {
            if (s < 9 && lim < lds32(sb + SM_HIST + (s * kWarps + warp) * 4)) {
                const uint4 v = lds128(sb + SM_REC + s * (kWarps * 512) + tid * 16);
                st_relaxed(g_rec + cta * (kG * 32) + s * kThreads + tid, v.x, v.y, v.z, v.w);
            }
        };
#pragma unroll
        for (int s = 0; s < kSendFirst; s++) send(s);
        cp_wait<0>();
        TSTAMP(12);
        __syncthreads();
        uint32_t mx = project(sb, warp, lane, [&](int step) { send(kSendFirst + step); if (step == 11) hdr = ld_relaxed32(hdrp); }, tw);
        if (warp < 8) {
            put_table(tw, warp, lane, nbase, ncta);
            mx = __reduce_max_sync(~0u, mx);
            if (lane == 0) asm volatile("red.shared.max.u32 [%0], %1;" :: "r"(sb + SM_MISC), "r"(mx) : "memory");
        }
    }
    TSTAMP(13);
#pragma unroll
    for (int q = 0; q < 2; q++) {
        const int i = tid + q * kThreads, r = i >> 3, c = i & 7;
        cp16(sb + SM_WH + r * 128 + ((c ^ (r & 7)) << 4), (const uint4*)w_h + (q ? 64 + feat(r - 64) : r) * 8 + c);
    }
    cp_commit();
    __syncthreads();
    TSTAMP(3);

    auto place = [&](uint32_t w0, uint32_t x, uint32_t ebase, uint32_t rank) {
        asm volatile("{.reg .pred p; setp.lt.u32 p, %3, %4; @p st.shared.u32 [%0], %1; @p st.shared.u32 [%0+%5], %2;}"
                     :: "r"(sb + SM_LS + (x & 31) * (kCapW * 4) + rank * 4), "r"(w0 & 0x7FFFu),
                        "r"(((w0 >> 15) + ebase) | ((x << 23) & 0x70000000u)), "r"(rank), "n"(kCapW), "n"(kLQ) : "memory");
    };
    unsigned spin = 0;
    if (warp == kWarps - 1) {
        if (lane == 0) {
            asm volatile("fence.acq_rel.gpu;" ::: "memory");
            asm volatile("st.relaxed.gpu.global.u16 [%0], %1;" :: "l"((unsigned short*)g_flag0 + cta), "h"((unsigned short)(tag | (lds32(sb + SM_MISC) >> 23))) : "memory");
        }
        __syncwarp();
        TSTAMP(2);
#pragma unroll
        for (int r = 0; r < 17; r++) {
            const uint32_t w = lds32(sb + SM_WE + (128 + r) * 128 + (((feat(2 * lane) >> 1) ^ ((r & 7) << 2)) << 2));
            sts32(sb + SM_W3 + r * 128 + ((lane ^ ((r & 7) << 2)) << 2), bf2h(hmul2(w, 0x3F003F00u)));
        }
        __nanosleep(800);
        const uint32_t tag2 = (tag & 0xFF00u) * 0x10001u;
        uint4 v;
        do {
            asm volatile("ld.acquire.gpu.global.v4.u32 {%0,%1,%2,%3}, [%4];" : "=r"(v.x), "=r"(v.y), "=r"(v.z), "=r"(v.w) : "l"(g_flag0 + min(lane, 16)) : "memory");
            if (lane >= 16) v.z = v.w = v.x;
            v.x ^= tag2; v.y ^= tag2; v.z ^= tag2; v.w ^= tag2;
            if (++spin > kSpinLimit) __trap();
        } while ((v.x | v.y | v.z | v.w) & 0xFF00FF00u);
        uint32_t mx = __vmaxu2(__vmaxu2(v.x, v.y), __vmaxu2(v.z, v.w));
        mx = max(mx & 255, mx >> 16);
        mx = __reduce_max_sync(~0u, mx);
        if (lane == 0) sts32(sb + SM_MISC + 4, mx);
        TSTAMP(4);
    } else {
        const uint4* recp = g_rec + (warp * kG + cta) * 32 + (lane ^ (cta & 7));
        while ((hdr ^ (epoch << 26)) >> 26) {
            hdr = ld_relaxed32(hdrp);
            if (++spin > kSpinLimit) __trap();
        }
        hdr = lane * kCol + warp < kG ? hdr & 0x3FFFFFFu : 0u;
        uint4 rv[kSegPerWarp];
        uint32_t cnt[kSegPerWarp];
#pragma unroll
        for (int s = 0; s < kSegPerWarp; s++) {
            cnt[s] = __shfl_sync(~0u, hdr, s) & 0x1FFF;
            rv[s] = make_uint4(0, tag, 0, tag);
            if (2 * lane < cnt[s]) rv[s] = ld_relaxed(recp + s * (kCol * kG * 32));
        }
        if (lane < kSegPerWarp) sts32(sb + SM_SEG + (lane * kCol + warp) * 4, hdr);
        uint32_t ovb = __ballot_sync(~0u, (hdr & 0x1FFF) > 64);
        uint4 ov = make_uint4(0, 0, 0, 0), ov2 = ov;
        if (ovb) {
            const int s1 = __ffs(ovb) - 1, s2 = __ffs(ovb & (ovb - 1)) - 1;
            if (lane < (__shfl_sync(~0u, hdr, s1) >> 13)) ov = ld_relaxed(g_ovf + (s1 * kCol + warp) * kChunk + lane);
            if (lane < (__shfl_sync(~0u, hdr, s2) >> 13)) ov2 = ld_relaxed(g_ovf + (s2 * kCol + warp) * kChunk + lane);
        }
        uint32_t rk[kSegPerWarp][2];
#pragma unroll
        for (int s = 0; s < kSegPerWarp + PD; s++) {
            if (s < kSegPerWarp) {
                while (__any_sync(~0u, (rv[s].y ^ tag) >= 256 || ((rv[s].w ^ tag) >= 256 && 2 * lane + 1 < cnt[s]))) {
                    if (2 * lane < cnt[s]) rv[s] = ld_relaxed(recp + s * (kCol * kG * 32));
                    if (++spin > kSpinLimit) __trap();
                }
                if (s == 0) TSTAMP(9);
                rk[s][0] = atoms_inc_lt(sb + SM_WCNT + (rv[s].y & 31) * 4, 2 * lane, cnt[s]);
                rk[s][1] = atoms_inc_lt(sb + SM_WCNT + (rv[s].w & 31) * 4, 2 * lane + 1, cnt[s]);
            }
            if (s >= PD) {
                place(rv[s - PD].x, rv[s - PD].y, ((s - PD) * kCol + warp) * kChunk, rk[s - PD][0]);
                place(rv[s - PD].z, rv[s - PD].w, ((s - PD) * kCol + warp) * kChunk, rk[s - PD][1]);
            }
        }
        TSTAMP(5);
        for (; ovb; ovb &= ovb - 1) {
            const uint32_t sg = __shfl_sync(~0u, hdr, __ffs(ovb) - 1), b = (__ffs(ovb) - 1) * kCol + warp;
            for (uint32_t i = lane; i < (sg >> 13); i += 32) {
                while (((ov.y ^ tag) | (ov.w ^ tag)) >= 256) {
                    ov = ld_relaxed(g_ovf + b * kChunk + i);
                    if (++spin > kSpinLimit) __trap();
                }
                if (ov.z == cta) place(ov.x, ov.y, b * kChunk, atoms_inc(sb + SM_WCNT + (ov.y & 31) * 4));
                ov.y = 0;
            }
            ov = ov2;
            ov2.y = 0;
        }
        TSTAMP(10);
    }
    uint32_t aw[4][4], w3[4][4];
    uint32_t wx[4];
#pragma unroll
    for (int j = 0; j < 4; j++) wx[j] = bf2h(lds16(sb + SM_WX + feat(16 * j + g) * 2) | (lds16(sb + SM_WX + feat(16 * j + 8 + g) * 2) << 16));
    cp_wait<0>();
    __syncthreads();
    TSTAMP(6);

    if (tid == 0) g_epoch[cta] = epoch;

    int w2;
    {
        const uint32_t key = (lds32(sb + SM_WCNT + lane * 4) << 5) | lane;
        const int r1 = __popc(__ballot_sync(~0u, key < __shfl_sync(~0u, key, warp)) & 0xFFFFu);
        const uint32_t key2 = __shfl_sync(~0u, key, lane | 16);
        int r2 = 0;
#pragma unroll
        for (int j = 0; j < 8; j++) r2 += __shfl_sync(~0u, key, 16 + ((lane >> 4) << 3) + j) > key2;
        r2 += __shfl_xor_sync(~0u, r2, 16);
        w2 = __ffs(__ballot_sync(~0u, r2 == r1)) - 1;
        const int k = lane & 7, j = lane < 16 ? k : 8 + (k >> 1);
        const int r = j < 6 ? warp + 32 * j : w2 + 16 + 32 * (j - 6), u = (lane >> 3) & 1, r3 = 1 + k + ((lane >> 4) << 3);
        const uint32_t a = lane >= 16 && (k & 1) ? sb + SM_W3 + (u << 4) : sb + SM_A + r * 128 + ((u ^ ((r + (r >> 5)) & 7)) << 4);
#pragma unroll
        for (int i = 0; i < 4; i++) {
            ldsm4t(aw[i], a ^ (i << 5));
            ldsm4t(w3[i], (sb + SM_W3 + r3 * 128 + ((u ^ (r3 & 7)) << 4)) ^ (i << 5));
        }
    }
    const uint32_t lsb = sb + SM_LS + warp * (kCapW * 4);
    const uint32_t stb = sb + SM_STAGE + warp * kStageBytes;
    const int lx = lane ^ ((lane >> 1) & 4) ^ (lane >> 4);
    const uint32_t cpB_ = stb + (lx << 4);
    const uint32_t ldB_ = stb + g * 128 + ((t ^ ((g & 1) << 2) ^ (g >> 1)) << 4);
    const uint32_t ldT_ = stb + ((lane & 7) + ((lane >> 4) << 3)) * 128 + ((((lane >> 3) & 1) ^ ((lane & 1) << 2) ^ ((lane >> 1) & 3)) << 4);
    const uint32_t ldE_ = stb + 2048 + ((lane & 7) + ((lane >> 4) << 3)) * 32 + ((((lane >> 3) ^ (lane >> 2)) & 1) << 4);
    uint32_t ohb = (lane & 8) ? sb + SM_POS + warp * kPosStride : sb + SM_OH;
    const uint32_t tabo = (lane & 7) << 4, eao = ((lx ^ (lane >> 3)) & 1) << 4;
    uint64_t tabp = (uint64_t)__cvta_generic_to_global(g_tab) + tabo;
    uint64_t eap = (uint64_t)__cvta_generic_to_global(e_attr) + eao;
    sts128(stb + 1024 + lane * 16, (uint32_t)tabp, (uint32_t)(tabp >> 32), (uint32_t)eap, (uint32_t)(eap >> 32));
    asm volatile("ld.volatile.shared.v2.u64 {%0,%1}, [%2];" : "=l"(tabp), "=l"(eap) : "r"(stb + 1024 + lane * 16) : "memory");
    sts128(stb + 512 + lane * 16, wx[0], wx[1], wx[2], wx[3]);
    { const uint4 w = lds128v(stb + 512 + lane * 16); wx[0] = w.x; wx[1] = w.y; wx[2] = w.z; wx[3] = w.w; }
    sts128(stb + lane * 16, cpB_, cpB_ ^ 32, ldB_, ldE_);
    sts128(stb + 1536 + lane * 16, ldT_, ldT_ ^ 32, ldT_ ^ 64, ldT_ ^ 96);
    const uint4 ad = lds128v(stb + lane * 16), at = lds128v(stb + 1536 + lane * 16);
    const uint32_t cpB = ad.x, cpB2 = ad.y, ldB = ad.z, ldE = ad.w, ldT[4] = {at.x, at.y, at.z, at.w};
    float acc[4][4], accp[4];
#pragma unroll
    for (int i = 0; i < 4; i++) { acc[i][0] = acc[i][1] = acc[i][2] = acc[i][3] = 0.f; accp[i] = 0.f; }
    auto switch_window = [&]() {
        __syncwarp();
        const int lane = fresh_lane();
        sts128(lsb + lane * 16, pack_bf16(acc[0][0], acc[0][1]), pack_bf16(acc[0][2], acc[0][3]), pack_bf16(acc[1][0], acc[1][1]), pack_bf16(acc[1][2], acc[1][3]));
        sts128(lsb + 512 + lane * 16, pack_bf16(acc[2][0], acc[2][1]), pack_bf16(acc[2][2], acc[2][3]), pack_bf16(acc[3][0], acc[3][1]), pack_bf16(acc[3][2], acc[3][3]));
        sts32(lsb + kLQ + lane * 4, pack_bf16(128.f * accp[0], 128.f * accp[1]));
#pragma unroll
        for (int i = 0; i < 4; i++) { acc[i][0] = acc[i][1] = acc[i][2] = acc[i][3] = 0.f; accp[i] = 0.f; }
#pragma unroll
        for (int j = 0; j < 3; j++) {
            const int r = j * 4 + (lane >> 3), hi = r < 6 ? r : r - 6, c = lane & 7, dloc = (r < 6 ? warp : 16 + w2) + 32 * hi;
            const bool ok = dloc < ncta;
            cp16z((r < 6 ? lsb + kLQ + 128 : sb + SM_H2 + warp * 768) + hi * 128 + ((c ^ hi) << 4), (const uint4*)h + (size_t)(ok ? nbase + dloc : 0) * 8 + c, ok ? 0u : ~0u);
        }
        ohb = ((lane & 8) ? sb + SM_POS + w2 * kPosStride : sb + SM_OH) + 128;
    };
    uint32_t pS, pQ, pD, qd;
    auto issue = [&](int lo, int st, bool on) {
        const uint4 s4 = lds128(pS + lo);
        const uint32_t q = lds32(pQ + lo);
        cp16g<128>(cpB + st, tabp, s4.x, on);
        cp16g<128>(cpB2 + st + 512, tabp, s4.y, on);
        cp16g<128>(cpB + st + 1024, tabp, s4.z, on);
        cp16g<128>(cpB2 + st + 1536, tabp, s4.w, on);
        cp16g<32>(cpB + st + 2048, eap, q & 0xFFFFFFu, on);
        cp_commit();
    };
    auto tile = [&](int sc, int lo, bool on) {
        const uint32_t oa = ohb + (qd >> 24);
        uint32_t oh[4], s0, s1;
        ldsm4(oh, oa);
        ldsm2t(s0, s1, oa + 256);
        cp_wait<2>();
        __syncwarp();
        uint32_t ef[4], pa, pb;
        const uint4 x0 = lds128(ldB + sc), x1 = lds128(ldB + sc + 1024);
        ldsm4(ef, ldE + sc);
        uint32_t c[4][4];
#pragma unroll
        for (int i = 0; i < 4; i++) ldsm4t(c[i], ldT[i] + sc);
#pragma unroll
        for (int i = 0; i < 4; i++) ef[i] = bf2h(ef[i]);
        const uint32_t d0 = hsub2(oh[3], __byte_perm(bitsel<0x003F003Fu>(bitsel<0x00070007u>(x0.x, x0.y << 3), x0.z << 6), 0, 0x2044));
        const uint32_t d1 = hsub2(oh[1], __byte_perm(bitsel<0x003F003Fu>(bitsel<0x00070007u>(x1.x, x1.y << 3), x1.z << 6), 0, 0x2044));
        const uint32_t q0 = bf2h(hmul2(d0, d0)), q1 = bf2h(hmul2(d1, d1));
        auto pre = [&](int i) {
            mma_h(c[i][0], c[i][1], w3[i], ef[0], ef[1]);
            mma_h(c[i][2], c[i][3], w3[i], ef[2], ef[3]);
            mma_h(c[i][0], c[i][1], aw[i], oh[0], q0);
            mma_h(c[i][2], c[i][3], aw[i], oh[2], q1);
        };
        auto act = [&](int i) {
#pragma unroll
            for (int q = 0; q < 4; q++) c[i][q] = silu_half2(c[i][q]);
            mma_f16(acc[i], c[i], s0, s1);
            pa = hfma2_hi(c[i][1], wx[i], hfma2_lo(c[i][0], wx[i], i ? pa : 0u));
            pb = hfma2_hi(c[i][3], wx[i], hfma2_lo(c[i][2], wx[i], i ? pb : 0u));
        };
        pre(0);
        pre(1);
        act(0);
        pre(2);
        act(1);
        pre(3);
        act(2);
        __syncwarp();
        qd = lds32(pD + lo + 64);
        issue(lo + 192, sc, on);
        act(3);
        float cs[4];
        mma_f16_k8_init(cs, movm(pa), movm(pb), 0x3C003C00u);
        const uint32_t cp = pack_bf16(cs[0], cs[2]);
        const uint32_t v0 = hmul2_lo(d0, cp), v1 = hmul2_hi(d1, cp);
        mma_bf16(accp, movm(v0), v0, movm(v1), v1, s0, s1);
    };
    bool synced = false;
    for (;;) {
        int sched, delta = 0;
        uint32_t first;
        __syncwarp();
        const int lane = fresh_lane();
        const uint32_t lsb2 = sb + SM_LS + (16 + w2) * (kCapW * 4);
        const uint32_t cnt0 = __reduce_max_sync(~0u, lds32(sb + SM_WCNT + warp * 4)), cnt1 = __reduce_max_sync(~0u, lds32(sb + SM_WCNT + 64 + w2 * 4));
        if (cnt0 <= kCapW && cnt1 <= kCapW) {
            const int n0 = (cnt0 + 15) >> 4, n1 = (cnt1 + 15) >> 4;
            const int i = (lane < 16 ? cnt0 : cnt1) + (lane & 15);
            const uint32_t a = (lane < 16 ? lsb : lsb2) + i * 4;
            if (i < 16 * (lane < 16 ? n0 : n1)) { sts32(a, nbase); sts32(a + kLQ, kPadQ | e0); }
            first = lsb; sched = n0 | ((n0 + n1) << 8); delta = lsb2 - lsb - 64 * n0;
            sched |= 1 << 29;
        } else {
            const uint32_t cur = __reduce_max_sync(~0u, lds32(sb + SM_CUR + warp * 4));
            int n = 0, cur_win = cur >> 24, cur_seg = (cur >> 16) & 255, cur_pos = cur & 0xFFFF;
            while (cur_seg < kG && n <= kCapW - 48) {
                const uint32_t sg = __reduce_max_sync(~0u, lds32(sb + SM_SEG + cur_seg * 4));
                const int len = 64 + ((sg & 0x1FFF) > 64 ? sg >> 13 : 0), i = cur_pos + lane;
                uint2 v = make_uint2(0, 255);
                if (i < 64) { if (i < (int)(sg & 0x1FFF)) v = __ldcg((const uint2*)g_rec + (cur_seg * kG + cta) * 64 + (i ^ ((2 * cta) & 14))); }
                else if (i < len) {
                    const uint4 o = __ldcg(g_ovf + cur_seg * kChunk + i - 64);
                    if (o.z == cta) v = make_uint2(o.x, o.y);
                }
                const bool hit = (v.y & 255) != 255 && (int)(v.y & 31) == (cur_win ? 16 + w2 : warp);
                const uint32_t bal = __ballot_sync(~0u, hit);
                if (hit) {
                    const int k = n + __popc(bal & ((1u << lane) - 1));
                    sts32(lsb2 + k * 4, v.x & 0x7FFFu);
                    sts32(lsb2 + kLQ + k * 4, ((v.x >> 15) + cur_seg * kChunk) | ((v.y << 23) & 0x70000000u));
                }
                n += __popc(bal);
                cur_pos += 32;
                if (cur_pos >= len) { cur_pos = 0; cur_seg++; }
            }
            if (lane < 16) { sts32(lsb2 + (n + lane) * 4, nbase); sts32(lsb2 + kLQ + (n + lane) * 4, kPadQ | e0); }
            const int nt = (n + 15) >> 4;
            first = lsb2; sched = 255 | (nt << 8);
            uint32_t nxt = (cur_win << 24) | (cur_seg << 16) | cur_pos;
            if (cur_seg == kG) {
                if (cur_win == 0) { sched = nt | (nt << 8); nxt = 1u << 24; } else sched |= 1 << 29;
            }
            __syncwarp();
            if (lane == 0) sts32(sb + SM_CUR + warp * 4, nxt);
        }
        __syncwarp();
        pS = first + (lane >> 3) * 16;
        const int pe = (lane ^ ((lane >> 1) & 4)) >> 1, pd = (lane ^ ((lane >> 1) & 8)) & 15;
        pQ = first + kLQ + (4 * (pe & 3) + (pe >> 2)) * 4;
        pD = first + kLQ + (4 * (pd & 3) + (pd >> 2)) * 4;
        sched = __reduce_max_sync(~0u, sched);
        const int n0 = (int8_t)sched * 64, nt = ((sched >> 8) & 255) * 64, ntm = __reduce_max_sync(~0u, nt - 192);
        if (n0 == 0) { pS += delta; pQ += delta; pD += delta; }
        issue(0, 0, nt > 0);
        qd = lds32(pD);
        if (n0 == 64) { pS += delta; pQ += delta; }
        issue(64, kStageStride, nt > 64);
        if (!synced) { __syncthreads(); synced = true; }
        if (n0 == 128) { pS += delta; pQ += delta; }
        issue(128, 2 * kStageStride, nt > 128);
        int sc = 0, ev = 0;
#pragma unroll 1
        for (int lo = 0;; lo += 64) {
            if (__builtin_expect(lo == ev, 0)) {
                if (lo == n0 - 192) { pS += delta; pQ += delta; }
                if (lo == n0 - 64) pD += delta;
                if (lo == n0) switch_window();
                if (lo == nt) break;
                ev = lo < n0 - 192 ? n0 - 192 : lo < n0 ? lo + 64 : nt;
            }
            tile(sc, lo, lo < ntm);
            sc = sc == 2 * kStageStride ? 0 : sc + kStageStride;
        }
        if (sched & (1 << 29)) break;
    }
    TSTAMP(7);

    {
        const int lane = fresh_lane(), g = lane >> 2, t = lane & 3;
        uint4 ma = lds128(lsb + lane * 16), mb = lds128(lsb + 512 + lane * 16);
        {
            uint32_t z = hadd2(hadd2(hadd2(ma.x, ma.y), hadd2(ma.z, ma.w)), hadd2(hadd2(mb.x, mb.y), hadd2(mb.z, mb.w)));
            z = hadd2(z, lds32(lsb + kLQ + lane * 4));
            float f = accp[0] + accp[1];
#pragma unroll
            for (int i = 0; i < 4; i++) f += (acc[i][0] + acc[i][1]) + (acc[i][2] + acc[i][3]);
            f += __uint_as_float(z << 16) + __uint_as_float(z & 0xFFFF0000u);
            if (__any_sync(~0u, !(fabsf(f) < __int_as_float(0x7F800000)) || lds32(sb + SM_MISC + 4) >= 127 + 15)) {
                float* buf = (float*)(smem + SM_STAGE + kStageStride + warp * kStageBytes);
#pragma unroll 1
                for (int sub = 0; sub < 2; sub++) {
                    exact_window(h, pos, e_attr, w_e, w_x, (const uint32_t*)(smem + SM_SEG), buf, sub ? 16 + w2 : warp);
#pragma unroll
                    for (int i = 0; i < 4; i++)
#pragma unroll
                        for (int q = 0; q < 4; q++) acc[i][q] = t < 3 ? buf[(2 * t + (q & 1)) * 64 + feat(16 * i + 8 * (q >> 1) + g)] : 0.f;
                    accp[0] = t < 3 ? buf[384 + 8 * t + (g >> 1)] * (1.f / 128.f) : 0.f;
                    accp[1] = t < 3 ? buf[388 + 8 * t + (g >> 1)] * (1.f / 128.f) : 0.f;
                    if (sub == 0) switch_window();
                    __syncwarp();
                }
                ma = lds128(lsb + lane * 16); mb = lds128(lsb + 512 + lane * 16);
            }
        }
        const uint32_t m0[4][2] = {{ma.x, ma.y}, {ma.z, ma.w}, {mb.x, mb.y}, {mb.z, mb.w}};
        float c[8][4];
#pragma unroll
        for (int j = 0; j < 8; j++) { c[j][0] = c[j][1] = c[j][2] = c[j][3] = 0.f; }
        uint32_t hf[4][4];
#pragma unroll
        for (int kk = 0; kk < 8; kk++) {
            const int ks = kk ^ 4;
            uint32_t a[4];
            if (ks < 4) {
                if (ks == 0) { cp_commit(); cp_wait<0>(); __syncwarp(); }
                const int hi = min(lane & 7, 5);
                ldsm4(hf[ks], ((lane & 8) ? sb + SM_H2 + warp * 768 : lsb + kLQ + 128) + hi * 128 + (((2 * ks + (lane >> 4)) ^ hi) << 4));
                a[0] = hf[ks][0]; a[1] = hf[ks][1]; a[2] = hf[ks][2]; a[3] = hf[ks][3];
            } else {
                const int i = ks - 4;
                a[0] = movm(m0[i][0]);
                a[1] = movm(pack_bf16(acc[i][0], acc[i][1]));
                a[2] = movm(m0[i][1]);
                a[3] = movm(pack_bf16(acc[i][2], acc[i][3]));
            }
#pragma unroll
            for (int i = 0; i < 4; i++) {
                uint32_t w[4];
                const int k = 16 * ks + (lane & 7) + ((lane >> 4) << 3);
                ldsm4t(w, sb + SM_WH + k * 128 + (((2 * i + ((lane >> 3) & 1)) ^ (k & 7)) << 4));
                mma_bf16(c[2 * i], a[0], a[1], a[2], a[3], w[0], w[2]);
                mma_bf16(c[2 * i + 1], a[0], a[1], a[2], a[3], w[1], w[3]);
            }
            if (kk == 3 && (g & 1) && g < 6 && t < 3) {
                const uint32_t dl[2] = {lds32(lsb + kLQ + lane * 4), pack_bf16(128.f * accp[0], 128.f * accp[1])};
#pragma unroll
                for (int sub = 0; sub < 2; sub++) {
                    const uint32_t pa = sb + SM_POS + (sub ? w2 : warp) * kPosStride + sub * 128 + t * 32 + (g >> 1) * 4;
                    const uint32_t o = hadd2(__byte_perm(lds32(pa), lds32(pa + 16), 0x7632), dl[sub]);
                    const int dloc = (sub ? 16 + w2 : warp) + 64 * t;
                    unsigned short* op = (unsigned short*)out_pos + (size_t)(nbase + dloc) * 3 + (g >> 1);
                    if (dloc < ncta) op[0] = (unsigned short)o;
                    if (dloc + 32 < ncta) op[96] = (unsigned short)(o >> 16);
                }
            }
        }
        __syncwarp();
#pragma unroll
        for (int ks = 0; ks < 4; ks++) {
            uint32_t o[4];
#pragma unroll
            for (int q = 0; q < 4; q++) {
                const float* cc = c[2 * ks + (q >> 1)] + 2 * (q & 1);
                o[q] = hadd2(hf[ks][q], pack_bf16(silu_half(0.5f * cc[0]), silu_half(0.5f * cc[1])));
            }
            const int r = lane & 15;
            stsm4(stb + r * 128 + (((2 * ks + (lane >> 4)) ^ (r & 7)) << 4), o[0], o[1], o[2], o[3]);
        }
        __syncwarp();
#pragma unroll
        for (int j = 0; j < 4; j++) {
            const int r = j * 4 + (lane >> 3), cc = lane & 7, dloc = (j < 2 ? warp : 16 + w2) + 32 * (r & 7);
            const uint4 v = lds128(stb + r * 128 + ((cc ^ (r & 7)) << 4));
            if (dloc < ncta) ((uint4*)out_h)[(size_t)(nbase + dloc) * 8 + cc] = v;
        }
    }
    TSTAMP(8);
}

}

extern "C" void kernel_launch(void* const* d_in, const int* in_sizes, int n_in, void* d_out, int out_size) {
    static bool init = false;
    if (!init) {
        cudaFuncSetAttribute(egnn_kernel, cudaFuncAttributeMaxDynamicSharedMemorySize, SM_TOTAL);
        init = true;
    }
    __nv_bfloat16* out = (__nv_bfloat16*)d_out;
    egnn_kernel<<<kG, kThreads, SM_TOTAL>>>(
        (const __nv_bfloat16*)d_in[0], (const __nv_bfloat16*)d_in[1], (const __nv_bfloat16*)d_in[2],
        (const int*)d_in[3], (const int*)d_in[4], (const __nv_bfloat16*)d_in[5],
        (const __nv_bfloat16*)d_in[6], (const __nv_bfloat16*)d_in[7], out, out + (size_t)kN * 64);
}
```
